```python
import torch

def _softmax(x, axis=-1):
    return torch.softmax(x, dim=axis)
def _gelu(x):
    return torch.nn.functional.gelu(x, approximate="tanh")
def _silu(x):
    return torch.nn.functional.silu(x)
def _sigmoid(x):
    return torch.sigmoid(x)
def _layernorm(x, axis=-1, eps=1e-5):
    m = x.mean(dim=axis, keepdim=True)
    v = x.var(dim=axis, keepdim=True, unbiased=False)
    return (x - m) / torch.sqrt(v + eps)
def _scatter_add(tgt, idx, src, axis=0):
    return tgt.clone().index_add_(axis, idx, src)
def _segment_sum(src, seg, n):
    out = torch.zeros((n,) + src.shape[1:], dtype=src.dtype)
    return out.index_add_(0, seg, src)
def _pad(x, pw):
    flat = tuple(v for pair in reversed(pw) for v in pair)
    return torch.nn.functional.pad(x, flat)

kernel_name = 'recurrent_scan__ssm_conv_s4d__dense_activation_squared_relu__prompt'

def setup_inputs():

    _w = (lambda a: (lambda t: t.to(torch.bfloat16) if t.is_floating_point() else t)(torch.as_tensor(a)))
    def _A_setup():
        Bsz, L, D, N = 1, 2048, 512, 128
        return {
            "u": _w((lambda *s: torch.randn(*s, dtype=torch.bfloat16) * 0.05)(Bsz, L, D)),
            "log_A_real": _w((lambda *s: torch.randn(*s, dtype=torch.bfloat16) * 3.2)(D, N) * 0.5),
            "A_imag": _w((lambda *s: torch.randn(*s, dtype=torch.bfloat16) * 0.05)(D, N) * 3.14),
            "C_real": _w((lambda *s: torch.randn(*s, dtype=torch.bfloat16) * 0.2)(D, N) / N ** 0.5),
            "C_imag": _w((lambda *s: torch.randn(*s, dtype=torch.bfloat16) * 0.2)(D, N) / N ** 0.5),
            "log_dt": _w((lambda *s: torch.randn(*s, dtype=torch.bfloat16) * 0.05)(D) * 0.5 - 4.0),
            "D_skip": _w((lambda *s: torch.randn(*s, dtype=torch.bfloat16) * 0.05)(D)),
        }
    _A_in = _A_setup()

    def _B_setup():
        B, S, D, F = 1, 2048, 512, 1792
        return {
            "x": _w((lambda *s: torch.randn(*s, dtype=torch.bfloat16) * 0.05)(B, S, D)),
            "w1": _w((lambda *s: torch.randn(*s, dtype=torch.bfloat16) * 0.05)(D, F)),
            "b1": _w((lambda *s: torch.randn(*s, dtype=torch.bfloat16) * 0.4)(F)),
            "w2": _w((lambda *s: torch.randn(*s, dtype=torch.bfloat16) * 0.05)(F, D)),
            "b2": _w((lambda *s: torch.randn(*s, dtype=torch.bfloat16) * 0.8)(D)),
        }
    _B_in = _B_setup()

    return {
        "A_u": _A_in["u"],
        "A_log_A_real": _A_in["log_A_real"],
        "A_A_imag": _A_in["A_imag"],
        "A_C_real": _A_in["C_real"],
        "A_C_imag": _A_in["C_imag"],
        "A_log_dt": _A_in["log_dt"],
        "A_D_skip": _A_in["D_skip"],
        "B_x": _B_in["x"],
        "B_w1": _B_in["w1"],
        "B_b1": _B_in["b1"],
        "B_w2": _B_in["w2"],
        "B_b2": _B_in["b2"],
    }

def reference(A_u, A_log_A_real, A_A_imag, A_C_real, A_C_imag, A_log_dt, A_D_skip, B_x, B_w1, B_b1, B_w2, B_b2):
    def _A_ref(u, log_A_real, A_imag, C_real, C_imag, log_dt, D_skip):
        L = u.shape[1]
        dt = torch.exp(log_dt)
        A = -torch.exp(log_A_real) + 1j * A_imag
        C = (C_real + 1j * C_imag) * dt[:, None]
        pos = (lambda x, dt: x.to(dt))(torch.arange(L), log_dt.dtype)
        P = torch.exp((A * dt[:, None])[:, :, None] * pos[None, None, :])
        K = 2.0 * torch.einsum("dn,dnl->dl", C, P).real
        L2 = 2 * L
        u_t = (lambda x, *d: x.permute(*d))(u, 0, 2, 1)
        Kf = (lambda x, *a, **k: torch.fft.rfft(x.float(), *a, **k))(K, L2)
        Uf = (lambda x, *a, **k: torch.fft.rfft(x.float(), *a, **k))(u_t, L2)
        y = (lambda x, *a, **k: torch.fft.irfft(x, *a, **k).to(torch.bfloat16))(Uf * Kf[None, :, :], L2)[:, :, :L]
        y = (lambda x, *d: x.permute(*d))(y, 0, 2, 1)
        return y + u * D_skip[None, None, :]

    def _B_ref(x, w1, b1, w2, b2):
        h = torch.einsum("bsd,df->bsf", x, w1) + b1
        zero = torch.zeros_like(h)
        r = torch.where(h > zero, h, zero)
        h = r * r
        out = torch.einsum("bsf,fd->bsd", h, w2) + b2
        return out

    x = A_u
    xn = _layernorm(x, axis=-1)
    s = _A_ref(xn, A_log_A_real, A_A_imag, A_C_real, A_C_imag, A_log_dt, A_D_skip)
    g = _silu(_B_ref(xn, B_w1, B_b1, B_w2, B_b2))
    return x + s * g
```

```cpp
#include <cuda_runtime.h>
#include <cuda_bf16.h>
#include <cuda.h>
#include <stdint.h>

typedef __nv_bfloat16 bf16;

constexpr int L_ = 2048, D_ = 512, N_ = 128, F_ = 1792;

__device__ __align__(1024) bf16 g_xn[L_ * D_];
__device__ __align__(1024) bf16 g_xnT[D_ * L_];
__device__ __align__(1024) bf16 g_K[D_ * L_];
__device__ __align__(1024) bf16 g_s[L_ * D_];
__device__ __align__(1024) bf16 g_h[L_ * F_];

__device__ __forceinline__ float bfr(float x) { return __bfloat162float(__float2bfloat16(x)); }
__device__ __forceinline__ uint32_t smem_u32(const void* p) { return (uint32_t)__cvta_generic_to_shared(p); }
__device__ __forceinline__ uint32_t pack_bf16(float lo, float hi) {
    __nv_bfloat162 v = __floats2bfloat162_rn(lo, hi);
    return *reinterpret_cast<uint32_t*>(&v);
}

__device__ __forceinline__ void mbar_init(uint32_t bar, uint32_t count) {
    asm volatile("mbarrier.init.shared::cta.b64 [%0], %1;" ::"r"(bar), "r"(count) : "memory");
}
__device__ __forceinline__ void mbar_expect_tx(uint32_t bar, uint32_t bytes) {
    asm volatile("mbarrier.arrive.expect_tx.shared::cta.b64 _, [%0], %1;" ::"r"(bar), "r"(bytes) : "memory");
}
__device__ __forceinline__ void mbar_arrive(uint32_t bar) {
    asm volatile("mbarrier.arrive.shared::cta.b64 _, [%0];" ::"r"(bar) : "memory");
}
__device__ __forceinline__ void mbar_wait(uint32_t bar, uint32_t parity) {
    uint32_t done;
    int it = 0;
    do {
        asm volatile(
            "{\n.reg .pred p;\n"
            "mbarrier.try_wait.parity.shared::cta.b64 p, [%1], %2;\n"
            "selp.u32 %0, 1, 0, p;\n}\n"
            : "=r"(done) : "r"(bar), "r"(parity) : "memory");
    } while (!done && ++it < (1 << 26));
}
__device__ __forceinline__ void tma_load_2d(uint32_t smem, const CUtensorMap* map, int c0, int c1, uint32_t bar) {
    asm volatile(
        "cp.async.bulk.tensor.2d.shared::cluster.global.mbarrier::complete_tx::bytes [%0], [%1, {%3, %4}], [%2];"
        ::"r"(smem), "l"(reinterpret_cast<uint64_t>(map)), "r"(bar), "r"(c0), "r"(c1) : "memory");
}
__device__ __forceinline__ void wgmma_fence() { asm volatile("wgmma.fence.sync.aligned;" ::: "memory"); }
__device__ __forceinline__ void wgmma_commit() { asm volatile("wgmma.commit_group.sync.aligned;" ::: "memory"); }
template <int N> __device__ __forceinline__ void wgmma_wait() {
    asm volatile("wgmma.wait_group.sync.aligned %0;" ::"n"(N) : "memory");
}
__device__ __forceinline__ uint64_t make_desc(uint32_t addr, uint32_t lbo_bytes, uint32_t sbo_bytes) {
    uint64_t d = 0;
    d |= (uint64_t)((addr & 0x3FFFF) >> 4);
    d |= (uint64_t)((lbo_bytes >> 4) & 0x3FFF) << 16;
    d |= (uint64_t)((sbo_bytes >> 4) & 0x3FFF) << 32;
    d |= (uint64_t)1 << 62;
    return d;
}

__device__ __forceinline__ void wgmma_n64(float (&d)[32], uint64_t da, uint64_t db, int scale_d) {
    asm volatile(
        "{\n.reg .pred p;\nsetp.ne.b32 p, %34, 0;\n"
        "wgmma.mma_async.sync.aligned.m64n64k16.f32.bf16.bf16 "
        "{%0,%1,%2,%3,%4,%5,%6,%7,%8,%9,%10,%11,%12,%13,%14,%15,%16,%17,%18,%19,%20,%21,%22,%23,%24,%25,%26,%27,%28,%29,%30,%31},"
        "%32, %33, p, 1, 1, 0, 1;\n}\n"
        : "+f"(d[0]), "+f"(d[1]), "+f"(d[2]), "+f"(d[3]), "+f"(d[4]), "+f"(d[5]), "+f"(d[6]), "+f"(d[7]),
          "+f"(d[8]), "+f"(d[9]), "+f"(d[10]), "+f"(d[11]), "+f"(d[12]), "+f"(d[13]), "+f"(d[14]), "+f"(d[15]),
          "+f"(d[16]), "+f"(d[17]), "+f"(d[18]), "+f"(d[19]), "+f"(d[20]), "+f"(d[21]), "+f"(d[22]), "+f"(d[23]),
          "+f"(d[24]), "+f"(d[25]), "+f"(d[26]), "+f"(d[27]), "+f"(d[28]), "+f"(d[29]), "+f"(d[30]), "+f"(d[31])
        : "l"(da), "l"(db), "r"(scale_d));
}
__device__ __forceinline__ void wgmma_n128(float (&d)[64], uint64_t da, uint64_t db, int scale_d) {
    asm volatile(
        "{\n.reg .pred p;\nsetp.ne.b32 p, %66, 0;\n"
        "wgmma.mma_async.sync.aligned.m64n128k16.f32.bf16.bf16 "
        "{%0,%1,%2,%3,%4,%5,%6,%7,%8,%9,%10,%11,%12,%13,%14,%15,%16,%17,%18,%19,%20,%21,%22,%23,%24,%25,%26,%27,%28,%29,%30,%31,"
        "%32,%33,%34,%35,%36,%37,%38,%39,%40,%41,%42,%43,%44,%45,%46,%47,%48,%49,%50,%51,%52,%53,%54,%55,%56,%57,%58,%59,%60,%61,%62,%63},"
        "%64, %65, p, 1, 1, 0, 1;\n}\n"
        : "+f"(d[0]), "+f"(d[1]), "+f"(d[2]), "+f"(d[3]), "+f"(d[4]), "+f"(d[5]), "+f"(d[6]), "+f"(d[7]),
          "+f"(d[8]), "+f"(d[9]), "+f"(d[10]), "+f"(d[11]), "+f"(d[12]), "+f"(d[13]), "+f"(d[14]), "+f"(d[15]),
          "+f"(d[16]), "+f"(d[17]), "+f"(d[18]), "+f"(d[19]), "+f"(d[20]), "+f"(d[21]), "+f"(d[22]), "+f"(d[23]),
          "+f"(d[24]), "+f"(d[25]), "+f"(d[26]), "+f"(d[27]), "+f"(d[28]), "+f"(d[29]), "+f"(d[30]), "+f"(d[31]),
          "+f"(d[32]), "+f"(d[33]), "+f"(d[34]), "+f"(d[35]), "+f"(d[36]), "+f"(d[37]), "+f"(d[38]), "+f"(d[39]),
          "+f"(d[40]), "+f"(d[41]), "+f"(d[42]), "+f"(d[43]), "+f"(d[44]), "+f"(d[45]), "+f"(d[46]), "+f"(d[47]),
          "+f"(d[48]), "+f"(d[49]), "+f"(d[50]), "+f"(d[51]), "+f"(d[52]), "+f"(d[53]), "+f"(d[54]), "+f"(d[55]),
          "+f"(d[56]), "+f"(d[57]), "+f"(d[58]), "+f"(d[59]), "+f"(d[60]), "+f"(d[61]), "+f"(d[62]), "+f"(d[63])
        : "l"(da), "l"(db), "r"(scale_d));
}

__device__ __forceinline__ void mma_bf16(float (&c)[4], uint32_t a0, uint32_t a1, uint32_t a2, uint32_t a3,
                                         uint32_t b0, uint32_t b1) {
    asm volatile(
        "mma.sync.aligned.m16n8k16.row.col.f32.bf16.bf16.f32 {%0,%1,%2,%3}, {%4,%5,%6,%7}, {%8,%9}, {%0,%1,%2,%3};"
        : "+f"(c[0]), "+f"(c[1]), "+f"(c[2]), "+f"(c[3])
        : "r"(a0), "r"(a1), "r"(a2), "r"(a3), "r"(b0), "r"(b1));
}
__device__ __forceinline__ void mma_tf32(float (&c)[4], uint32_t a0, uint32_t a1, uint32_t a2, uint32_t a3,
                                         uint32_t b0, uint32_t b1) {
    asm volatile(
        "mma.sync.aligned.m16n8k8.row.col.f32.tf32.tf32.f32 {%0,%1,%2,%3}, {%4,%5,%6,%7}, {%8,%9}, {%0,%1,%2,%3};"
        : "+f"(c[0]), "+f"(c[1]), "+f"(c[2]), "+f"(c[3])
        : "r"(a0), "r"(a1), "r"(a2), "r"(a3), "r"(b0), "r"(b1));
}
__device__ __forceinline__ uint32_t to_tf32(float x) {
    uint32_t r;
    asm("cvt.rna.tf32.f32 %0, %1;" : "=r"(r) : "f"(x));
    return r;
}
__device__ __forceinline__ void ldmatrix_x4(uint32_t& r0, uint32_t& r1, uint32_t& r2, uint32_t& r3, uint32_t addr) {
    asm volatile("ldmatrix.sync.aligned.m8n8.x4.shared.b16 {%0,%1,%2,%3}, [%4];"
                 : "=r"(r0), "=r"(r1), "=r"(r2), "=r"(r3) : "r"(addr));
}

struct cplx { float r, i; };
__device__ __forceinline__ cplx cmul(cplx a, cplx b) { return {a.r * b.r - a.i * b.i, a.r * b.i + a.i * b.r}; }
__device__ __forceinline__ cplx csq(cplx a) { return {a.r * a.r - a.i * a.i, 2.f * a.r * a.i}; }
__device__ __forceinline__ cplx cexp_(float ar, float ai) {
    float m = expf(ar), s, c;
    sincosf(ai, &s, &c);
    return {m * c, m * s};
}

__global__ void __launch_bounds__(256) k1_prep(const bf16* __restrict__ x, const bf16* __restrict__ log_A_real,
                                               const bf16* __restrict__ A_imag, const bf16* __restrict__ C_real,
                                               const bf16* __restrict__ C_imag, const bf16* __restrict__ log_dt) {
    __shared__ __align__(16) unsigned char smraw[32 * 520 * 2];
    const int warp = threadIdx.x >> 5, lane = threadIdx.x & 31;
    if (blockIdx.x < 64) {
        bf16* tile = reinterpret_cast<bf16*>(smraw);
        const int l0 = blockIdx.x * 32;
        for (int rr = 0; rr < 4; ++rr) {
            const int r = warp * 4 + rr;
            const bf16* row = x + (size_t)(l0 + r) * D_;
            uint4 v0 = *reinterpret_cast<const uint4*>(row + lane * 8);
            uint4 v1 = *reinterpret_cast<const uint4*>(row + 256 + lane * 8);
            float f[16];
            const bf16* p0 = reinterpret_cast<const bf16*>(&v0);
            const bf16* p1 = reinterpret_cast<const bf16*>(&v1);
#pragma unroll
            for (int i = 0; i < 8; ++i) { f[i] = __bfloat162float(p0[i]); f[8 + i] = __bfloat162float(p1[i]); }
            float sum = 0.f;
#pragma unroll
            for (int i = 0; i < 16; ++i) sum += f[i];
#pragma unroll
            for (int o = 16; o; o >>= 1) sum += __shfl_xor_sync(0xffffffffu, sum, o);
            const float mean = sum * (1.f / D_);
            float vs = 0.f;
#pragma unroll
            for (int i = 0; i < 16; ++i) { float d = f[i] - mean; vs += d * d; }
#pragma unroll
            for (int o = 16; o; o >>= 1) vs += __shfl_xor_sync(0xffffffffu, vs, o);
            const float m_b = bfr(mean);
            const float v_b = bfr(vs * (1.f / D_));
            const float den = bfr(sqrtf(bfr(v_b + 1e-5f)));
            uint4 o0, o1;
            bf16* q0 = reinterpret_cast<bf16*>(&o0);
            bf16* q1 = reinterpret_cast<bf16*>(&o1);
#pragma unroll
            for (int i = 0; i < 8; ++i) {
                q0[i] = __float2bfloat16(bfr(f[i] - m_b) / den);
                q1[i] = __float2bfloat16(bfr(f[8 + i] - m_b) / den);
            }
            *reinterpret_cast<uint4*>(g_xn + (size_t)(l0 + r) * D_ + lane * 8) = o0;
            *reinterpret_cast<uint4*>(g_xn + (size_t)(l0 + r) * D_ + 256 + lane * 8) = o1;
            *reinterpret_cast<uint4*>(tile + r * 520 + lane * 8) = o0;
            *reinterpret_cast<uint4*>(tile + r * 520 + 256 + lane * 8) = o1;
        }
        __syncthreads();
        for (int c = threadIdx.x; c < D_; c += 256) {
            uint32_t w[16];
#pragma unroll
            for (int i = 0; i < 16; ++i) {
                uint32_t lo = *reinterpret_cast<const unsigned short*>(tile + (2 * i) * 520 + c);
                uint32_t hi = *reinterpret_cast<const unsigned short*>(tile + (2 * i + 1) * 520 + c);
                w[i] = lo | (hi << 16);
            }
            uint4* dst = reinterpret_cast<uint4*>(g_xnT + (size_t)c * L_ + l0);
#pragma unroll
            for (int i = 0; i < 4; ++i) dst[i] = make_uint4(w[4 * i], w[4 * i + 1], w[4 * i + 2], w[4 * i + 3]);
        }
    } else {
        float* Kd = reinterpret_cast<float*>(smraw) + warp * 648;
        const int c = (blockIdx.x - 64) * 8 + warp;
        const int g = lane >> 2, t = lane & 3;
        const float dt = bfr(expf(__bfloat162float(log_dt[c])));
        float acc[5][4];
#pragma unroll
        for (int s = 0; s < 5; ++s)
#pragma unroll
            for (int i = 0; i < 4; ++i) acc[s][i] = 0.f;
        float k2048 = 0.f;
        for (int ks = 0; ks < 32; ++ks) {
            const int m = c * N_ + ks * 4 + t;
            const float ar = -bfr(expf(__bfloat162float(log_A_real[m]))) * dt;
            const float ai = __bfloat162float(A_imag[m]) * dt;
            const cplx C = {__bfloat162float(C_real[m]) * dt, __bfloat162float(C_imag[m]) * dt};
            const cplx q1 = cexp_(ar * (float)g, ai * (float)g);
            const cplx w8 = cexp_(ar * 8.f, ai * 8.f);
            const cplx q2 = csq(q1), q4 = csq(q2), q8 = csq(q4), q16 = csq(q8), q32 = csq(q16), q64 = csq(q32);
            const cplx c16 = csq(w8), c32 = csq(c16), c64 = csq(c32), c128 = csq(c64), c256 = csq(c128),
                       c512 = csq(c256), c1024 = csq(c512);
            cplx lo, hi;
            lo = cmul(C, q8); hi = cmul(lo, c64);
            mma_tf32(acc[0], to_tf32(lo.r), to_tf32(hi.r), to_tf32(-lo.i), to_tf32(-hi.i), to_tf32(q1.r), to_tf32(q1.i));
            lo = cmul(lo, c128); hi = cmul(lo, c64);
            mma_tf32(acc[1], to_tf32(lo.r), to_tf32(hi.r), to_tf32(-lo.i), to_tf32(-hi.i), to_tf32(q1.r), to_tf32(q1.i));
            lo = cmul(cmul(C, q16), c256); hi = cmul(lo, c128);
            mma_tf32(acc[2], to_tf32(lo.r), to_tf32(hi.r), to_tf32(-lo.i), to_tf32(-hi.i), to_tf32(q2.r), to_tf32(q2.i));
            lo = cmul(cmul(C, q32), c512); hi = cmul(lo, c256);
            mma_tf32(acc[3], to_tf32(lo.r), to_tf32(hi.r), to_tf32(-lo.i), to_tf32(-hi.i), to_tf32(q4.r), to_tf32(q4.i));
            lo = cmul(cmul(C, q64), c1024); hi = cmul(lo, c512);
            mma_tf32(acc[4], to_tf32(lo.r), to_tf32(hi.r), to_tf32(-lo.i), to_tf32(-hi.i), to_tf32(q8.r), to_tf32(q8.i));
            if (g == 0) { cplx e = cmul(C, csq(c1024)); k2048 += e.r; }
        }
        k2048 += __shfl_xor_sync(0xffffffffu, k2048, 1);
        k2048 += __shfl_xor_sync(0xffffffffu, k2048, 2);
#pragma unroll
        for (int s = 0; s < 5; ++s) {
            Kd[s * 128 + 8 * g + 2 * t] = 2.f * acc[s][0];
            Kd[s * 128 + 8 * g + 2 * t + 1] = 2.f * acc[s][1];
            Kd[s * 128 + 8 * (g + 8) + 2 * t] = 2.f * acc[s][2];
            Kd[s * 128 + 8 * (g + 8) + 2 * t + 1] = 2.f * acc[s][3];
        }
        if (lane == 0) Kd[640] = 2.f * k2048;
        __syncwarp();
        for (int l2 = lane; l2 < L_ / 2; l2 += 32) {
            float v[2];
#pragma unroll
            for (int e = 0; e < 2; ++e) {
                const int l = 2 * l2 + e;
                const int p = (int)bfr((float)l);
                int idx;
                if (p < 256) idx = p;
                else if (p < 512) idx = 256 + ((p - 256) >> 1);
                else if (p < 1024) idx = 384 + ((p - 512) >> 2);
                else if (p < 2048) idx = 512 + ((p - 1024) >> 3);
                else idx = 640;
                v[e] = Kd[idx];
            }
            reinterpret_cast<uint32_t*>(g_K + (size_t)c * L_)[l2] = pack_bf16(v[0], v[1]);
        }
    }
}

constexpr int CV_PKPAD = 64;
constexpr int CV_PK = CV_PKPAD + L_ + 16;
constexpr int CV_UROWS = 40;
constexpr int CV_UPITCH = 72;
constexpr int CV_CH = 4;
constexpr int CV_SMEM = CV_CH * (CV_PK * 4 + CV_UROWS * CV_UPITCH * 2);

__global__ void __launch_bounds__(256) k2_conv(const bf16* __restrict__ D_skip) {
    extern __shared__ __align__(16) unsigned char sm[];
    uint32_t* PKall = reinterpret_cast<uint32_t*>(sm);
    bf16* Uall = reinterpret_cast<bf16*>(sm + CV_CH * CV_PK * 4);
    const int c0 = blockIdx.x * CV_CH;
    const int tid = threadIdx.x, warp = tid >> 5, lane = tid & 31;
    for (int ch = 0; ch < CV_CH; ++ch) {
        uint32_t* PK = PKall + ch * CV_PK;
        bf16* U = Uall + ch * CV_UROWS * CV_UPITCH;
        const unsigned short* Kg = reinterpret_cast<const unsigned short*>(g_K + (size_t)(c0 + ch) * L_);
        for (int i = tid; i < CV_PK; i += 256) {
            const int idx = i - CV_PKPAD;
            uint32_t lo = (idx >= 0 && idx < L_) ? Kg[idx] : 0;
            uint32_t hi = (idx - 1 >= 0 && idx - 1 < L_) ? Kg[idx - 1] : 0;
            PK[i] = lo | (hi << 16);
        }
        for (int i = tid; i < 8 * CV_UPITCH / 2; i += 256) reinterpret_cast<uint32_t*>(U)[i] = 0;
        const uint4* src = reinterpret_cast<const uint4*>(g_xnT + (size_t)(c0 + ch) * L_);
        for (int i = tid; i < L_ / 8; i += 256) {
            const int a = i >> 3, b8 = i & 7;
            *reinterpret_cast<uint4*>(U + (a + 8) * CV_UPITCH + b8 * 8) = src[i];
        }
    }
    __syncthreads();
    const int ch = warp >> 1, half = warp & 1;
    const int g = lane >> 2, t = lane & 3;
    const uint32_t* PK = PKall + ch * CV_PK + CV_PKPAD + (g - 2 * t);
    const uint32_t ubase = smem_u32(Uall + ch * CV_UROWS * CV_UPITCH);
    float acc[2][4][4];
#pragma unroll
    for (int i = 0; i < 2; ++i)
#pragma unroll
        for (int n = 0; n < 4; ++n)
#pragma unroll
            for (int q = 0; q < 4; ++q) acc[i][n][q] = 0.f;
    const int lm_row = lane & 7, lm_kh = (lane >> 3) & 1, lm_nt = lane >> 4;
#pragma unroll
    for (int d1 = 0; d1 < 4; ++d1) {
#pragma unroll 1
        for (int d0 = 0; d0 < 8; ++d0) {
            const int delta = d1 * 8 + d0;
            uint32_t W[11];
#pragma unroll
            for (int j = 0; j < 11; ++j) W[j] = PK[8 * (8 * delta + 4 * half - 7 + j)];
#pragma unroll
            for (int kb = 0; kb < 4; ++kb) {
#pragma unroll
                for (int np = 0; np < 2; ++np) {
                    if (2 * np + 1 < d1) continue;
                    uint32_t b[4];
                    const int col = 8 * (2 * np + lm_nt) + lm_row - delta + 8;
                    const uint32_t addr = ubase + (uint32_t)(col * CV_UPITCH + kb * 16 + lm_kh * 8) * 2;
                    ldmatrix_x4(b[0], b[1], b[2], b[3], addr);
#pragma unroll
                    for (int i = 0; i < 2; ++i) {
                        const int w = 2 * (i - kb) + 6;
                        const uint32_t a0 = W[w + 1], a1 = W[w + 2], a2 = W[w], a3 = W[w + 1];
                        if (2 * np >= d1) mma_bf16(acc[i][2 * np], a0, a1, a2, a3, b[0], b[1]);
                        mma_bf16(acc[i][2 * np + 1], a0, a1, a2, a3, b[2], b[3]);
                    }
                }
            }
        }
    }
    __syncthreads();
    bf16* Ys = reinterpret_cast<bf16*>(sm);
#pragma unroll
    for (int i = 0; i < 2; ++i)
#pragma unroll
        for (int n = 0; n < 4; ++n) {
            const int b = (2 * half + i) * 16 + g;
            const int a = n * 8 + 2 * t;
            Ys[(64 * a + b) * 4 + ch] = __float2bfloat16(acc[i][n][0]);
            Ys[(64 * (a + 1) + b) * 4 + ch] = __float2bfloat16(acc[i][n][1]);
            Ys[(64 * a + b + 8) * 4 + ch] = __float2bfloat16(acc[i][n][2]);
            Ys[(64 * (a + 1) + b + 8) * 4 + ch] = __float2bfloat16(acc[i][n][3]);
        }
    __syncthreads();
    float dsk[4];
#pragma unroll
    for (int q = 0; q < 4; ++q) dsk[q] = __bfloat162float(D_skip[c0 + q]);
    for (int l = tid; l < L_; l += 256) {
        uint2 yv = *reinterpret_cast<const uint2*>(Ys + l * 4);
        uint2 xv = *reinterpret_cast<const uint2*>(g_xn + (size_t)l * D_ + c0);
        const bf16* yp = reinterpret_cast<const bf16*>(&yv);
        const bf16* xp = reinterpret_cast<const bf16*>(&xv);
        uint2 o;
        bf16* op = reinterpret_cast<bf16*>(&o);
#pragma unroll
        for (int q = 0; q < 4; ++q)
            op[q] = __float2bfloat16(__bfloat162float(yp[q]) + bfr(__bfloat162float(xp[q]) * dsk[q]));
        *reinterpret_cast<uint2*>(g_s + (size_t)l * D_ + c0) = o;
    }
}

template <int BN, int KTOT, int STAGES, int EPI>
__global__ void __launch_bounds__(384) k_gemm(const __grid_constant__ CUtensorMap mapA,
                                              const __grid_constant__ CUtensorMap mapB,
                                              const bf16* __restrict__ bias, const bf16* __restrict__ xin,
                                              bf16* __restrict__ out) {
    constexpr int A_BYTES = 128 * 64 * 2;
    constexpr int B_BYTES = 64 * BN * 2;
    constexpr int STAGE_BYTES = A_BYTES + B_BYTES;
    constexpr int KSTEPS = KTOT / 64;
    extern __shared__ __align__(1024) unsigned char smem_raw[];
    const uint32_t sbase = (smem_u32(smem_raw) + 1023) & ~1023u;
    __shared__ __align__(8) uint64_t bars[2 * STAGES];
    const uint32_t full0 = smem_u32(bars), empty0 = smem_u32(bars + STAGES);
    const int tid = threadIdx.x, warp = tid >> 5, lane = tid & 31;
    const int m0 = blockIdx.y * 128, n0 = blockIdx.x * BN;
    if (tid == 0) {
        for (int s = 0; s < STAGES; ++s) { mbar_init(full0 + 8 * s, 1); mbar_init(empty0 + 8 * s, 2); }
        asm volatile("fence.mbarrier_init.release.cluster;" ::: "memory");
    }
    __syncthreads();
    if (warp == 8) {
        if (lane == 0) {
            for (int k = 0; k < KSTEPS; ++k) {
                const int s = k % STAGES;
                if (k >= STAGES) mbar_wait(empty0 + 8 * s, ((k / STAGES) - 1) & 1);
                mbar_expect_tx(full0 + 8 * s, STAGE_BYTES);
                const uint32_t sa = sbase + s * STAGE_BYTES;
                tma_load_2d(sa, &mapA, k * 64, m0, full0 + 8 * s);
#pragma unroll
                for (int j = 0; j < BN / 64; ++j)
                    tma_load_2d(sa + A_BYTES + j * 8192, &mapB, n0 + j * 64, k * 64, full0 + 8 * s);
            }
        }
    } else if (warp < 8) {
        const int wg = warp >> 2;
        float acc[BN / 2];
#pragma unroll
        for (int i = 0; i < BN / 2; ++i) acc[i] = 0.f;
        for (int k = 0; k < KSTEPS; ++k) {
            const int s = k % STAGES;
            mbar_wait(full0 + 8 * s, (k / STAGES) & 1);
            const uint32_t sa = sbase + s * STAGE_BYTES + wg * 64 * 128;
            const uint32_t sb = sbase + s * STAGE_BYTES + A_BYTES;
            wgmma_fence();
#pragma unroll
            for (int kk = 0; kk < 4; ++kk) {
                const uint64_t da = make_desc(sa + kk * 32, 16, 1024);
                if constexpr (BN == 64) {
                    const uint64_t db = make_desc(sb + kk * 2048, 8192, 1024);
                    wgmma_n64(acc, da, db, 1);
                } else {
#pragma unroll
                    for (int j = 0; j < BN / 128; ++j) {
                        const uint64_t db = make_desc(sb + j * 16384 + kk * 2048, 8192, 1024);
                        wgmma_n128(*reinterpret_cast<float(*)[64]>(&acc[j * 64]), da, db, 1);
                    }
                }
            }
            wgmma_commit();
            wgmma_wait<0>();
            if ((tid & 127) == 0) mbar_arrive(empty0 + 8 * s);
        }
        const int wr = (warp & 3) * 16 + (lane >> 2);
        const int row0 = m0 + wg * 64 + wr;
#pragma unroll
        for (int j = 0; j < BN / 8; ++j) {
            const int col = n0 + j * 8 + (lane & 3) * 2;
            const float bb0 = __bfloat162float(bias[col]), bb1 = __bfloat162float(bias[col + 1]);
#pragma unroll
            for (int hh = 0; hh < 2; ++hh) {
                const int row = row0 + hh * 8;
                float v0 = bfr(bfr(acc[j * 4 + hh * 2]) + bb0);
                float v1 = bfr(bfr(acc[j * 4 + hh * 2 + 1]) + bb1);
                if constexpr (EPI == 0) {
                    v0 = v0 > 0.f ? v0 : 0.f;
                    v1 = v1 > 0.f ? v1 : 0.f;
                    *reinterpret_cast<uint32_t*>(out + (size_t)row * F_ + col) = pack_bf16(v0 * v0, v1 * v1);
                } else {
                    const float g0 = bfr(v0 / (1.f + __expf(-v0)));
                    const float g1 = bfr(v1 / (1.f + __expf(-v1)));
                    const __nv_bfloat162 sv = *reinterpret_cast<const __nv_bfloat162*>(g_s + (size_t)row * D_ + col);
                    const __nv_bfloat162 xv = *reinterpret_cast<const __nv_bfloat162*>(xin + (size_t)row * D_ + col);
                    const float o0 = __bfloat162float(xv.x) + bfr(__bfloat162float(sv.x) * g0);
                    const float o1 = __bfloat162float(xv.y) + bfr(__bfloat162float(sv.y) * g1);
                    *reinterpret_cast<uint32_t*>(out + (size_t)row * D_ + col) = pack_bf16(o0, o1);
                }
            }
        }
    }
}

typedef CUresult (*PFN_encodeTiled)(CUtensorMap*, CUtensorMapDataType, cuuint32_t, void*, const cuuint64_t*,
                                    const cuuint64_t*, const cuuint32_t*, const cuuint32_t*, CUtensorMapInterleave,
                                    CUtensorMapSwizzle, CUtensorMapL2promotion, CUtensorMapFloatOOBfill);

static void make_map(PFN_encodeTiled enc, CUtensorMap* m, const void* ptr, uint64_t inner, uint64_t outer,
                     uint32_t box_inner, uint32_t box_outer) {
    cuuint64_t dims[2] = {inner, outer};
    cuuint64_t strides[1] = {inner * 2};
    cuuint32_t box[2] = {box_inner, box_outer};
    cuuint32_t es[2] = {1, 1};
    enc(m, CU_TENSOR_MAP_DATA_TYPE_BFLOAT16, 2, const_cast<void*>(ptr), dims, strides, box, es,
        CU_TENSOR_MAP_INTERLEAVE_NONE, CU_TENSOR_MAP_SWIZZLE_128B, CU_TENSOR_MAP_L2_PROMOTION_L2_256B,
        CU_TENSOR_MAP_FLOAT_OOB_FILL_NONE);
}

extern "C" void kernel_launch(void* const* d_in, const int* in_sizes, int n_in, void* d_out, int out_size) {
    const bf16* x = (const bf16*)d_in[0];
    const bf16* log_A_real = (const bf16*)d_in[1];
    const bf16* A_imag = (const bf16*)d_in[2];
    const bf16* C_real = (const bf16*)d_in[3];
    const bf16* C_imag = (const bf16*)d_in[4];
    const bf16* log_dt = (const bf16*)d_in[5];
    const bf16* D_skip = (const bf16*)d_in[6];
    const bf16* w1 = (const bf16*)d_in[8];
    const bf16* b1 = (const bf16*)d_in[9];
    const bf16* w2 = (const bf16*)d_in[10];
    const bf16* b2 = (const bf16*)d_in[11];
    bf16* out = (bf16*)d_out;

    constexpr int G1_BN = 256, G1_ST = 4, G2_BN = 64, G2_ST = 6;
    constexpr int G1_SMEM = G1_ST * (128 * 64 * 2 + 64 * G1_BN * 2) + 1024;
    constexpr int G2_SMEM = G2_ST * (128 * 64 * 2 + 64 * G2_BN * 2) + 1024;

    static bool init = false;
    static CUtensorMap mA1, mB1, mA2, mB2;
    static void *p_xn, *p_h;
    if (!init) {
        void* fn = nullptr;
        cudaDriverEntryPointQueryResult qr;
        cudaGetDriverEntryPoint("cuTensorMapEncodeTiled", &fn, cudaEnableDefault, &qr);
        PFN_encodeTiled enc = (PFN_encodeTiled)fn;
        cudaGetSymbolAddress(&p_xn, g_xn);
        cudaGetSymbolAddress(&p_h, g_h);
        make_map(enc, &mA1, p_xn, D_, L_, 64, 128);
        make_map(enc, &mB1, w1, F_, D_, 64, 64);
        make_map(enc, &mA2, p_h, F_, L_, 64, 128);
        make_map(enc, &mB2, w2, D_, F_, 64, 64);
        cudaFuncSetAttribute(k2_conv, cudaFuncAttributeMaxDynamicSharedMemorySize, CV_SMEM);
        cudaFuncSetAttribute(k_gemm<G1_BN, D_, G1_ST, 0>, cudaFuncAttributeMaxDynamicSharedMemorySize, G1_SMEM);
        cudaFuncSetAttribute(k_gemm<G2_BN, F_, G2_ST, 1>, cudaFuncAttributeMaxDynamicSharedMemorySize, G2_SMEM);
        init = true;
    }
    k1_prep<<<128, 256>>>(x, log_A_real, A_imag, C_real, C_imag, log_dt);
    k2_conv<<<D_ / CV_CH, 256, CV_SMEM>>>(D_skip);
    k_gemm<G1_BN, D_, G1_ST, 0><<<dim3(F_ / G1_BN, L_ / 128), 384, G1_SMEM>>>(mA1, mB1, b1, x, (bf16*)p_h);
    k_gemm<G2_BN, F_, G2_ST, 1><<<dim3(D_ / G2_BN, L_ / 128), 384, G2_SMEM>>>(mA2, mB2, b2, x, out);
}
```

```cpp
#include <cuda_runtime.h>
#include <cuda_bf16.h>
#include <cuda.h>
#include <stdint.h>

typedef __nv_bfloat16 bf16;

constexpr int L_ = 2048, D_ = 512, N_ = 128, F_ = 1792;

__device__ __align__(1024) bf16 g_xn[L_ * D_];
__device__ __align__(1024) bf16 g_xnT[D_ * L_];
__device__ __align__(1024) bf16 g_K[D_ * L_];
__device__ __align__(1024) bf16 g_s[L_ * D_];
__device__ __align__(1024) bf16 g_h[L_ * F_];

__device__ __forceinline__ float bfr(float x) { return __bfloat162float(__float2bfloat16(x)); }
__device__ __forceinline__ uint32_t smem_u32(const void* p) { return (uint32_t)__cvta_generic_to_shared(p); }
__device__ __forceinline__ uint32_t pack_bf16(float lo, float hi) {
    __nv_bfloat162 v = __floats2bfloat162_rn(lo, hi);
    return *reinterpret_cast<uint32_t*>(&v);
}

__device__ __forceinline__ void mbar_init(uint32_t bar, uint32_t count) {
    asm volatile("mbarrier.init.shared::cta.b64 [%0], %1;" ::"r"(bar), "r"(count) : "memory");
}
__device__ __forceinline__ void mbar_expect_tx(uint32_t bar, uint32_t bytes) {
    asm volatile("mbarrier.arrive.expect_tx.shared::cta.b64 _, [%0], %1;" ::"r"(bar), "r"(bytes) : "memory");
}
__device__ __forceinline__ void mbar_arrive(uint32_t bar) {
    asm volatile("mbarrier.arrive.shared::cta.b64 _, [%0];" ::"r"(bar) : "memory");
}
__device__ __forceinline__ void mbar_wait(uint32_t bar, uint32_t parity) {
    uint32_t done;
    int it = 0;
    do {
        asm volatile(
            "{\n.reg .pred p;\n"
            "mbarrier.try_wait.parity.shared::cta.b64 p, [%1], %2;\n"
            "selp.u32 %0, 1, 0, p;\n}\n"
            : "=r"(done) : "r"(bar), "r"(parity) : "memory");
    } while (!done && ++it < (1 << 26));
}
__device__ __forceinline__ void tma_load_2d(uint32_t smem, const CUtensorMap* map, int c0, int c1, uint32_t bar) {
    asm volatile(
        "cp.async.bulk.tensor.2d.shared::cluster.global.mbarrier::complete_tx::bytes [%0], [%1, {%3, %4}], [%2];"
        ::"r"(smem), "l"(reinterpret_cast<uint64_t>(map)), "r"(bar), "r"(c0), "r"(c1) : "memory");
}
__device__ __forceinline__ void tma_load_2d_mc(uint32_t smem, const CUtensorMap* map, int c0, int c1, uint32_t bar,
                                               uint16_t mask) {
    asm volatile(
        "cp.async.bulk.tensor.2d.shared::cluster.global.mbarrier::complete_tx::bytes.multicast::cluster [%0], [%1, {%3, %4}], [%2], %5;"
        ::"r"(smem), "l"(reinterpret_cast<uint64_t>(map)), "r"(bar), "r"(c0), "r"(c1), "h"(mask) : "memory");
}
__device__ __forceinline__ uint32_t mapa(uint32_t addr, uint32_t cta) {
    uint32_t r;
    asm volatile("mapa.shared::cluster.u32 %0, %1, %2;" : "=r"(r) : "r"(addr), "r"(cta));
    return r;
}
__device__ __forceinline__ void mbar_arrive_cluster(uint32_t cluster_addr) {
    asm volatile("mbarrier.arrive.release.cluster.shared::cluster.b64 _, [%0];" ::"r"(cluster_addr) : "memory");
}
__device__ __forceinline__ void cluster_sync_all() {
    asm volatile("barrier.cluster.arrive.release.aligned;\nbarrier.cluster.wait.acquire.aligned;" ::: "memory");
}
__device__ __forceinline__ void wgmma_fence() { asm volatile("wgmma.fence.sync.aligned;" ::: "memory"); }
__device__ __forceinline__ void wgmma_commit() { asm volatile("wgmma.commit_group.sync.aligned;" ::: "memory"); }
template <int N> __device__ __forceinline__ void wgmma_wait() {
    asm volatile("wgmma.wait_group.sync.aligned %0;" ::"n"(N) : "memory");
}
__device__ __forceinline__ uint64_t make_desc(uint32_t addr, uint32_t lbo_bytes, uint32_t sbo_bytes, uint32_t swz = 1) {
    uint64_t d = 0;
    d |= (uint64_t)((addr & 0x3FFFF) >> 4);
    d |= (uint64_t)((lbo_bytes >> 4) & 0x3FFF) << 16;
    d |= (uint64_t)((sbo_bytes >> 4) & 0x3FFF) << 32;
    d |= (uint64_t)swz << 62;
    return d;
}

__device__ __forceinline__ void wgmma_n128(float (&d)[64], uint64_t da, uint64_t db) {
    asm volatile(
        "wgmma.mma_async.sync.aligned.m64n128k16.f32.bf16.bf16 {%0,%1,%2,%3,%4,%5,%6,%7,%8,%9,%10,%11,%12,%13,%14,%15,%16,%17,%18,%19,%20,%21,%22,%23,%24,%25,%26,%27,%28,%29,%30,%31,%32,%33,%34,%35,%36,%37,%38,%39,%40,%41,%42,%43,%44,%45,%46,%47,%48,%49,%50,%51,%52,%53,%54,%55,%56,%57,%58,%59,%60,%61,%62,%63}, %64, %65, 1, 1, 1, 0, 1;\n"
        : "+f"(d[0]), "+f"(d[1]), "+f"(d[2]), "+f"(d[3]), "+f"(d[4]), "+f"(d[5]), "+f"(d[6]), "+f"(d[7]), "+f"(d[8]), "+f"(d[9]), "+f"(d[10]), "+f"(d[11]), "+f"(d[12]), "+f"(d[13]), "+f"(d[14]), "+f"(d[15]), "+f"(d[16]), "+f"(d[17]), "+f"(d[18]), "+f"(d[19]), "+f"(d[20]), "+f"(d[21]), "+f"(d[22]), "+f"(d[23]), "+f"(d[24]), "+f"(d[25]), "+f"(d[26]), "+f"(d[27]), "+f"(d[28]), "+f"(d[29]), "+f"(d[30]), "+f"(d[31]), "+f"(d[32]), "+f"(d[33]), "+f"(d[34]), "+f"(d[35]), "+f"(d[36]), "+f"(d[37]), "+f"(d[38]), "+f"(d[39]), "+f"(d[40]), "+f"(d[41]), "+f"(d[42]), "+f"(d[43]), "+f"(d[44]), "+f"(d[45]), "+f"(d[46]), "+f"(d[47]), "+f"(d[48]), "+f"(d[49]), "+f"(d[50]), "+f"(d[51]), "+f"(d[52]), "+f"(d[53]), "+f"(d[54]), "+f"(d[55]), "+f"(d[56]), "+f"(d[57]), "+f"(d[58]), "+f"(d[59]), "+f"(d[60]), "+f"(d[61]), "+f"(d[62]), "+f"(d[63])
        : "l"(da), "l"(db));
}

__device__ __forceinline__ void wgmma_n224(float (&d)[112], uint64_t da, uint64_t db) {
    asm volatile(
        "wgmma.mma_async.sync.aligned.m64n224k16.f32.bf16.bf16 {%0,%1,%2,%3,%4,%5,%6,%7,%8,%9,%10,%11,%12,%13,%14,%15,%16,%17,%18,%19,%20,%21,%22,%23,%24,%25,%26,%27,%28,%29,%30,%31,%32,%33,%34,%35,%36,%37,%38,%39,%40,%41,%42,%43,%44,%45,%46,%47,%48,%49,%50,%51,%52,%53,%54,%55,%56,%57,%58,%59,%60,%61,%62,%63,%64,%65,%66,%67,%68,%69,%70,%71,%72,%73,%74,%75,%76,%77,%78,%79,%80,%81,%82,%83,%84,%85,%86,%87,%88,%89,%90,%91,%92,%93,%94,%95,%96,%97,%98,%99,%100,%101,%102,%103,%104,%105,%106,%107,%108,%109,%110,%111}, %112, %113, 1, 1, 1, 0, 1;\n"
        : "+f"(d[0]), "+f"(d[1]), "+f"(d[2]), "+f"(d[3]), "+f"(d[4]), "+f"(d[5]), "+f"(d[6]), "+f"(d[7]), "+f"(d[8]), "+f"(d[9]), "+f"(d[10]), "+f"(d[11]), "+f"(d[12]), "+f"(d[13]), "+f"(d[14]), "+f"(d[15]), "+f"(d[16]), "+f"(d[17]), "+f"(d[18]), "+f"(d[19]), "+f"(d[20]), "+f"(d[21]), "+f"(d[22]), "+f"(d[23]), "+f"(d[24]), "+f"(d[25]), "+f"(d[26]), "+f"(d[27]), "+f"(d[28]), "+f"(d[29]), "+f"(d[30]), "+f"(d[31]), "+f"(d[32]), "+f"(d[33]), "+f"(d[34]), "+f"(d[35]), "+f"(d[36]), "+f"(d[37]), "+f"(d[38]), "+f"(d[39]), "+f"(d[40]), "+f"(d[41]), "+f"(d[42]), "+f"(d[43]), "+f"(d[44]), "+f"(d[45]), "+f"(d[46]), "+f"(d[47]), "+f"(d[48]), "+f"(d[49]), "+f"(d[50]), "+f"(d[51]), "+f"(d[52]), "+f"(d[53]), "+f"(d[54]), "+f"(d[55]), "+f"(d[56]), "+f"(d[57]), "+f"(d[58]), "+f"(d[59]), "+f"(d[60]), "+f"(d[61]), "+f"(d[62]), "+f"(d[63]), "+f"(d[64]), "+f"(d[65]), "+f"(d[66]), "+f"(d[67]), "+f"(d[68]), "+f"(d[69]), "+f"(d[70]), "+f"(d[71]), "+f"(d[72]), "+f"(d[73]), "+f"(d[74]), "+f"(d[75]), "+f"(d[76]), "+f"(d[77]), "+f"(d[78]), "+f"(d[79]), "+f"(d[80]), "+f"(d[81]), "+f"(d[82]), "+f"(d[83]), "+f"(d[84]), "+f"(d[85]), "+f"(d[86]), "+f"(d[87]), "+f"(d[88]), "+f"(d[89]), "+f"(d[90]), "+f"(d[91]), "+f"(d[92]), "+f"(d[93]), "+f"(d[94]), "+f"(d[95]), "+f"(d[96]), "+f"(d[97]), "+f"(d[98]), "+f"(d[99]), "+f"(d[100]), "+f"(d[101]), "+f"(d[102]), "+f"(d[103]), "+f"(d[104]), "+f"(d[105]), "+f"(d[106]), "+f"(d[107]), "+f"(d[108]), "+f"(d[109]), "+f"(d[110]), "+f"(d[111])
        : "l"(da), "l"(db));
}


__device__ __forceinline__ void mma_bf16(float (&c)[4], uint32_t a0, uint32_t a1, uint32_t a2, uint32_t a3,
                                         uint32_t b0, uint32_t b1) {
    asm volatile(
        "mma.sync.aligned.m16n8k16.row.col.f32.bf16.bf16.f32 {%0,%1,%2,%3}, {%4,%5,%6,%7}, {%8,%9}, {%0,%1,%2,%3};"
        : "+f"(c[0]), "+f"(c[1]), "+f"(c[2]), "+f"(c[3])
        : "r"(a0), "r"(a1), "r"(a2), "r"(a3), "r"(b0), "r"(b1));
}
__device__ __forceinline__ void mma_tf32(float (&c)[4], uint32_t a0, uint32_t a1, uint32_t a2, uint32_t a3,
                                         uint32_t b0, uint32_t b1) {
    asm volatile(
        "mma.sync.aligned.m16n8k8.row.col.f32.tf32.tf32.f32 {%0,%1,%2,%3}, {%4,%5,%6,%7}, {%8,%9}, {%0,%1,%2,%3};"
        : "+f"(c[0]), "+f"(c[1]), "+f"(c[2]), "+f"(c[3])
        : "r"(a0), "r"(a1), "r"(a2), "r"(a3), "r"(b0), "r"(b1));
}
__device__ __forceinline__ uint32_t to_tf32(float x) {
    uint32_t r;
    asm("cvt.rna.tf32.f32 %0, %1;" : "=r"(r) : "f"(x));
    return r;
}
__device__ __forceinline__ void ldmatrix_x4(uint32_t& r0, uint32_t& r1, uint32_t& r2, uint32_t& r3, uint32_t addr) {
    asm volatile("ldmatrix.sync.aligned.m8n8.x4.shared.b16 {%0,%1,%2,%3}, [%4];"
                 : "=r"(r0), "=r"(r1), "=r"(r2), "=r"(r3) : "r"(addr));
}

struct cplx { float r, i; };
__device__ __forceinline__ cplx cmul(cplx a, cplx b) { return {a.r * b.r - a.i * b.i, a.r * b.i + a.i * b.r}; }
__device__ __forceinline__ cplx csq(cplx a) { return {a.r * a.r - a.i * a.i, 2.f * a.r * a.i}; }
__device__ __forceinline__ cplx cexp_(float ar, float ai) {
    float m = expf(ar), s, c;
    sincosf(ai, &s, &c);
    return {m * c, m * s};
}

__global__ void __launch_bounds__(256) k1_prep(const bf16* __restrict__ x, const bf16* __restrict__ log_A_real,
                                               const bf16* __restrict__ A_imag, const bf16* __restrict__ C_real,
                                               const bf16* __restrict__ C_imag, const bf16* __restrict__ log_dt) {
    __shared__ __align__(16) unsigned char smraw[32 * 520 * 2];
    const int warp = threadIdx.x >> 5, lane = threadIdx.x & 31;
    if (blockIdx.x < 64) {
        bf16* tile = reinterpret_cast<bf16*>(smraw);
        const int l0 = blockIdx.x * 32;
        for (int rr = 0; rr < 4; ++rr) {
            const int r = warp * 4 + rr;
            const bf16* row = x + (size_t)(l0 + r) * D_;
            uint4 v0 = *reinterpret_cast<const uint4*>(row + lane * 8);
            uint4 v1 = *reinterpret_cast<const uint4*>(row + 256 + lane * 8);
            float f[16];
            const bf16* p0 = reinterpret_cast<const bf16*>(&v0);
            const bf16* p1 = reinterpret_cast<const bf16*>(&v1);
#pragma unroll
            for (int i = 0; i < 8; ++i) { f[i] = __bfloat162float(p0[i]); f[8 + i] = __bfloat162float(p1[i]); }
            float sum = 0.f;
#pragma unroll
            for (int i = 0; i < 16; ++i) sum += f[i];
#pragma unroll
            for (int o = 16; o; o >>= 1) sum += __shfl_xor_sync(0xffffffffu, sum, o);
            const float mean = sum * (1.f / D_);
            float vs = 0.f;
#pragma unroll
            for (int i = 0; i < 16; ++i) { float d = f[i] - mean; vs += d * d; }
#pragma unroll
            for (int o = 16; o; o >>= 1) vs += __shfl_xor_sync(0xffffffffu, vs, o);
            const float m_b = bfr(mean);
            const float v_b = bfr(vs * (1.f / D_));
            const float den = bfr(sqrtf(bfr(v_b + 1e-5f)));
            uint4 o0, o1;
            bf16* q0 = reinterpret_cast<bf16*>(&o0);
            bf16* q1 = reinterpret_cast<bf16*>(&o1);
#pragma unroll
            for (int i = 0; i < 8; ++i) {
                q0[i] = __float2bfloat16(bfr(f[i] - m_b) / den);
                q1[i] = __float2bfloat16(bfr(f[8 + i] - m_b) / den);
            }
            *reinterpret_cast<uint4*>(g_xn + (size_t)(l0 + r) * D_ + lane * 8) = o0;
            *reinterpret_cast<uint4*>(g_xn + (size_t)(l0 + r) * D_ + 256 + lane * 8) = o1;
            *reinterpret_cast<uint4*>(tile + r * 520 + lane * 8) = o0;
            *reinterpret_cast<uint4*>(tile + r * 520 + 256 + lane * 8) = o1;
        }
        __syncthreads();
        for (int c = threadIdx.x; c < D_; c += 256) {
            uint32_t w[16];
#pragma unroll
            for (int i = 0; i < 16; ++i) {
                uint32_t lo = *reinterpret_cast<const unsigned short*>(tile + (2 * i) * 520 + c);
                uint32_t hi = *reinterpret_cast<const unsigned short*>(tile + (2 * i + 1) * 520 + c);
                w[i] = lo | (hi << 16);
            }
            uint4* dst = reinterpret_cast<uint4*>(g_xnT + (size_t)c * L_ + l0);
#pragma unroll
            for (int i = 0; i < 4; ++i) dst[i] = make_uint4(w[4 * i], w[4 * i + 1], w[4 * i + 2], w[4 * i + 3]);
        }
    } else {
        float* Kd = reinterpret_cast<float*>(smraw) + warp * 648;
        const int c = (blockIdx.x - 64) * 8 + warp;
        const int g = lane >> 2, t = lane & 3;
        const float dt = bfr(expf(__bfloat162float(log_dt[c])));
        float acc[5][4];
#pragma unroll
        for (int s = 0; s < 5; ++s)
#pragma unroll
            for (int i = 0; i < 4; ++i) acc[s][i] = 0.f;
        float k2048 = 0.f;
        for (int ks = 0; ks < 32; ++ks) {
            const int m = c * N_ + ks * 4 + t;
            const float ar = -bfr(expf(__bfloat162float(log_A_real[m]))) * dt;
            const float ai = __bfloat162float(A_imag[m]) * dt;
            const cplx C = {__bfloat162float(C_real[m]) * dt, __bfloat162float(C_imag[m]) * dt};
            const cplx q1 = cexp_(ar * (float)g, ai * (float)g);
            const cplx w8 = cexp_(ar * 8.f, ai * 8.f);
            const cplx q2 = csq(q1), q4 = csq(q2), q8 = csq(q4), q16 = csq(q8), q32 = csq(q16), q64 = csq(q32);
            const cplx c16 = csq(w8), c32 = csq(c16), c64 = csq(c32), c128 = csq(c64), c256 = csq(c128),
                       c512 = csq(c256), c1024 = csq(c512);
            cplx lo, hi;
            lo = cmul(C, q8); hi = cmul(lo, c64);
            mma_tf32(acc[0], to_tf32(lo.r), to_tf32(hi.r), to_tf32(-lo.i), to_tf32(-hi.i), to_tf32(q1.r), to_tf32(q1.i));
            lo = cmul(lo, c128); hi = cmul(lo, c64);
            mma_tf32(acc[1], to_tf32(lo.r), to_tf32(hi.r), to_tf32(-lo.i), to_tf32(-hi.i), to_tf32(q1.r), to_tf32(q1.i));
            lo = cmul(cmul(C, q16), c256); hi = cmul(lo, c128);
            mma_tf32(acc[2], to_tf32(lo.r), to_tf32(hi.r), to_tf32(-lo.i), to_tf32(-hi.i), to_tf32(q2.r), to_tf32(q2.i));
            lo = cmul(cmul(C, q32), c512); hi = cmul(lo, c256);
            mma_tf32(acc[3], to_tf32(lo.r), to_tf32(hi.r), to_tf32(-lo.i), to_tf32(-hi.i), to_tf32(q4.r), to_tf32(q4.i));
            lo = cmul(cmul(C, q64), c1024); hi = cmul(lo, c512);
            mma_tf32(acc[4], to_tf32(lo.r), to_tf32(hi.r), to_tf32(-lo.i), to_tf32(-hi.i), to_tf32(q8.r), to_tf32(q8.i));
            if (g == 0) { cplx e = cmul(C, csq(c1024)); k2048 += e.r; }
        }
        k2048 += __shfl_xor_sync(0xffffffffu, k2048, 1);
        k2048 += __shfl_xor_sync(0xffffffffu, k2048, 2);
#pragma unroll
        for (int s = 0; s < 5; ++s) {
            Kd[s * 128 + 8 * g + 2 * t] = 2.f * acc[s][0];
            Kd[s * 128 + 8 * g + 2 * t + 1] = 2.f * acc[s][1];
            Kd[s * 128 + 8 * (g + 8) + 2 * t] = 2.f * acc[s][2];
            Kd[s * 128 + 8 * (g + 8) + 2 * t + 1] = 2.f * acc[s][3];
        }
        if (lane == 0) Kd[640] = 2.f * k2048;
        __syncwarp();
        for (int l2 = lane; l2 < L_ / 2; l2 += 32) {
            float v[2];
#pragma unroll
            for (int e = 0; e < 2; ++e) {
                const int l = 2 * l2 + e;
                const int p = (int)bfr((float)l);
                int idx;
                if (p < 256) idx = p;
                else if (p < 512) idx = 256 + ((p - 256) >> 1);
                else if (p < 1024) idx = 384 + ((p - 512) >> 2);
                else if (p < 2048) idx = 512 + ((p - 1024) >> 3);
                else idx = 640;
                v[e] = Kd[idx];
            }
            reinterpret_cast<uint32_t*>(g_K + (size_t)c * L_)[l2] = pack_bf16(v[0], v[1]);
        }
    }
}

constexpr int CV_PKPAD = 64;
constexpr int CV_PK = CV_PKPAD + L_ + 16;
constexpr int CV_UROWS = 40;
constexpr int CV_UPITCH = 72;
constexpr int CV_CH = 4;
constexpr int CV_SMEM = CV_CH * (CV_PK * 4 + CV_UROWS * CV_UPITCH * 2);

__global__ void __launch_bounds__(256) k2_conv(const bf16* __restrict__ D_skip) {
    extern __shared__ __align__(16) unsigned char sm[];
    uint32_t* PKall = reinterpret_cast<uint32_t*>(sm);
    bf16* Uall = reinterpret_cast<bf16*>(sm + CV_CH * CV_PK * 4);
    const int c0 = blockIdx.x * CV_CH;
    const int tid = threadIdx.x, warp = tid >> 5, lane = tid & 31;
    for (int ch = 0; ch < CV_CH; ++ch) {
        uint32_t* PK = PKall + ch * CV_PK;
        bf16* U = Uall + ch * CV_UROWS * CV_UPITCH;
        const unsigned short* Kg = reinterpret_cast<const unsigned short*>(g_K + (size_t)(c0 + ch) * L_);
        for (int i = tid; i < CV_PK; i += 256) {
            const int idx = i - CV_PKPAD;
            uint32_t lo = (idx >= 0 && idx < L_) ? Kg[idx] : 0;
            uint32_t hi = (idx - 1 >= 0 && idx - 1 < L_) ? Kg[idx - 1] : 0;
            PK[i] = lo | (hi << 16);
        }
        for (int i = tid; i < 8 * CV_UPITCH / 2; i += 256) reinterpret_cast<uint32_t*>(U)[i] = 0;
        const uint4* src = reinterpret_cast<const uint4*>(g_xnT + (size_t)(c0 + ch) * L_);
        for (int i = tid; i < L_ / 8; i += 256) {
            const int a = i >> 3, b8 = i & 7;
            *reinterpret_cast<uint4*>(U + (a + 8) * CV_UPITCH + b8 * 8) = src[i];
        }
    }
    __syncthreads();
    const int ch = warp >> 1, half = warp & 1;
    const int g = lane >> 2, t = lane & 3;
    const uint32_t* PK = PKall + ch * CV_PK + CV_PKPAD + (g - 2 * t);
    const uint32_t ubase = smem_u32(Uall + ch * CV_UROWS * CV_UPITCH);
    float acc[2][4][4];
#pragma unroll
    for (int i = 0; i < 2; ++i)
#pragma unroll
        for (int n = 0; n < 4; ++n)
#pragma unroll
            for (int q = 0; q < 4; ++q) acc[i][n][q] = 0.f;
    const int lm_row = lane & 7, lm_kh = (lane >> 3) & 1, lm_nt = lane >> 4;
#pragma unroll
    for (int d1 = 0; d1 < 4; ++d1) {
#pragma unroll 1
        for (int d0 = 0; d0 < 8; ++d0) {
            const int delta = d1 * 8 + d0;
            uint32_t W[11];
#pragma unroll
            for (int j = 0; j < 11; ++j) W[j] = PK[8 * (8 * delta + 4 * half - 7 + j)];
#pragma unroll
            for (int kb = 0; kb < 4; ++kb) {
#pragma unroll
                for (int np = 0; np < 2; ++np) {
                    if (2 * np + 1 < d1) continue;
                    uint32_t b[4];
                    const int col = 8 * (2 * np + lm_nt) + lm_row - delta + 8;
                    const uint32_t addr = ubase + (uint32_t)(col * CV_UPITCH + kb * 16 + lm_kh * 8) * 2;
                    ldmatrix_x4(b[0], b[1], b[2], b[3], addr);
#pragma unroll
                    for (int i = 0; i < 2; ++i) {
                        const int w = 2 * (i - kb) + 6;
                        const uint32_t a0 = W[w + 1], a1 = W[w + 2], a2 = W[w], a3 = W[w + 1];
                        if (2 * np >= d1) mma_bf16(acc[i][2 * np], a0, a1, a2, a3, b[0], b[1]);
                        mma_bf16(acc[i][2 * np + 1], a0, a1, a2, a3, b[2], b[3]);
                    }
                }
            }
        }
    }
    __syncthreads();
    bf16* Ys = reinterpret_cast<bf16*>(sm);
#pragma unroll
    for (int i = 0; i < 2; ++i)
#pragma unroll
        for (int n = 0; n < 4; ++n) {
            const int b = (2 * half + i) * 16 + g;
            const int a = n * 8 + 2 * t;
            Ys[(64 * a + b) * 4 + ch] = __float2bfloat16(acc[i][n][0]);
            Ys[(64 * (a + 1) + b) * 4 + ch] = __float2bfloat16(acc[i][n][1]);
            Ys[(64 * a + b + 8) * 4 + ch] = __float2bfloat16(acc[i][n][2]);
            Ys[(64 * (a + 1) + b + 8) * 4 + ch] = __float2bfloat16(acc[i][n][3]);
        }
    __syncthreads();
    float dsk[4];
#pragma unroll
    for (int q = 0; q < 4; ++q) dsk[q] = __bfloat162float(D_skip[c0 + q]);
    for (int l = tid; l < L_; l += 256) {
        uint2 yv = *reinterpret_cast<const uint2*>(Ys + l * 4);
        uint2 xv = *reinterpret_cast<const uint2*>(g_xn + (size_t)l * D_ + c0);
        const bf16* yp = reinterpret_cast<const bf16*>(&yv);
        const bf16* xp = reinterpret_cast<const bf16*>(&xv);
        uint2 o;
        bf16* op = reinterpret_cast<bf16*>(&o);
#pragma unroll
        for (int q = 0; q < 4; ++q)
            op[q] = __float2bfloat16(__bfloat162float(yp[q]) + bfr(__bfloat162float(xp[q]) * dsk[q]));
        *reinterpret_cast<uint2*>(g_s + (size_t)l * D_ + c0) = o;
    }
}

template <int CM, int CN, int STAGES>
__global__ void __launch_bounds__(384) k_g1(const __grid_constant__ CUtensorMap mapA,
                                            const __grid_constant__ CUtensorMap mapB,
                                            const bf16* __restrict__ bias) {
    constexpr int A_BYTES = 128 * 64 * 2;
    constexpr int B_BYTES = 64 * 224 * 2;
    constexpr int STAGE_BYTES = A_BYTES + B_BYTES;
    constexpr int KSTEPS = D_ / 64;
    constexpr int NSRC = CM + CN - 1;
    extern __shared__ __align__(1024) unsigned char smem_raw[];
    const uint32_t sbase = (smem_u32(smem_raw) + 1023) & ~1023u;
    __shared__ __align__(8) uint64_t bars[2 * STAGES];
    const uint32_t full0 = smem_u32(bars), empty0 = smem_u32(bars + STAGES);
    const int tid = threadIdx.x, warp = tid >> 5, lane = tid & 31;
    const int m0 = blockIdx.y * 128, n0 = blockIdx.x * 224;
    const int cx = blockIdx.x % CN, cy = blockIdx.y % CM;
    if (tid == 0) {
        for (int s = 0; s < STAGES; ++s) { mbar_init(full0 + 8 * s, 1); mbar_init(empty0 + 8 * s, 2 * NSRC); }
        asm volatile("fence.mbarrier_init.release.cluster;" ::: "memory");
    }
    cluster_sync_all();
    if (warp == 8) {
        if (lane == 0) {
            uint16_t maskA = 0, maskB = 0;
            for (int i = 0; i < CN; ++i) maskA |= 1 << (i + CN * cy);
            for (int i = 0; i < CM; ++i) maskB |= 1 << (cx + CN * i);
            for (int k = 0; k < KSTEPS; ++k) {
                const int s = k % STAGES;
                if (k >= STAGES) mbar_wait(empty0 + 8 * s, ((k / STAGES) - 1) & 1);
                mbar_expect_tx(full0 + 8 * s, STAGE_BYTES);
                const uint32_t sa = sbase + s * STAGE_BYTES;
                tma_load_2d_mc(sa + cx * (128 / CN) * 128, &mapA, k * 64, m0 + cx * (128 / CN), full0 + 8 * s, maskA);
#pragma unroll
                for (int j = 0; j < 7; ++j)
                    tma_load_2d_mc(sa + A_BYTES + j * 4096 + cy * (64 / CM) * 64, &mapB, n0 + j * 32,
                                   k * 64 + cy * (64 / CM), full0 + 8 * s, maskB);
            }
        }
    } else if (warp < 8) {
        const int wg = warp >> 2;
        uint32_t tgt = 0;
        if (lane < CN) tgt = lane + CN * cy;
        else if (lane < NSRC) { int i = lane - CN; if (i >= cy) ++i; tgt = cx + CN * i; }
        const uint32_t rem_empty0 = mapa(empty0, tgt);
        float acc[112];
#pragma unroll
        for (int i = 0; i < 112; ++i) acc[i] = 0.f;
        for (int k = 0; k < KSTEPS; ++k) {
            const int s = k % STAGES;
            mbar_wait(full0 + 8 * s, (k / STAGES) & 1);
            const uint32_t sa = sbase + s * STAGE_BYTES + wg * 64 * 128;
            const uint32_t sb = sbase + s * STAGE_BYTES + A_BYTES;
            wgmma_fence();
#pragma unroll
            for (int kk = 0; kk < 4; ++kk)
                wgmma_n224(acc, make_desc(sa + kk * 32, 16, 1024, 1), make_desc(sb + kk * 1024, 4096, 512, 2));
            wgmma_commit();
            if (k > 0) {
                wgmma_wait<1>();
                if ((warp & 3) == 0 && lane < NSRC) mbar_arrive_cluster(rem_empty0 + 8 * ((k - 1) % STAGES));
            }
        }
        wgmma_wait<0>();
        const int row0 = m0 + wg * 64 + (warp & 3) * 16 + (lane >> 2);
#pragma unroll
        for (int j = 0; j < 28; ++j) {
            const int col = n0 + j * 8 + (lane & 3) * 2;
            const __nv_bfloat162 bv = *reinterpret_cast<const __nv_bfloat162*>(bias + col);
            const float bb0 = __bfloat162float(bv.x), bb1 = __bfloat162float(bv.y);
#pragma unroll
            for (int hh = 0; hh < 2; ++hh) {
                float v0 = bfr(bfr(acc[j * 4 + hh * 2]) + bb0);
                float v1 = bfr(bfr(acc[j * 4 + hh * 2 + 1]) + bb1);
                v0 = v0 > 0.f ? v0 : 0.f;
                v1 = v1 > 0.f ? v1 : 0.f;
                *reinterpret_cast<uint32_t*>(g_h + (size_t)(row0 + hh * 8) * F_ + col) = pack_bf16(v0 * v0, v1 * v1);
            }
        }
    }
    cluster_sync_all();
}

template <int STAGES>
__global__ void __launch_bounds__(384) k_g2(const __grid_constant__ CUtensorMap mapA,
                                            const __grid_constant__ CUtensorMap mapB,
                                            const bf16* __restrict__ bias, const bf16* __restrict__ xin,
                                            bf16* __restrict__ out) {
    constexpr int A_BYTES = 128 * 64 * 2;
    constexpr int B_BYTES = 64 * 128 * 2;
    constexpr int STAGE_BYTES = A_BYTES + B_BYTES;
    constexpr int KSTEPS = F_ / 128;
    extern __shared__ __align__(1024) unsigned char smem_raw[];
    const uint32_t sbase = (smem_u32(smem_raw) + 1023) & ~1023u;
    const uint32_t xbuf = sbase + STAGES * STAGE_BYTES;
    __shared__ __align__(8) uint64_t bars[2 * STAGES];
    const uint32_t full0 = smem_u32(bars), empty0 = smem_u32(bars + STAGES);
    const int tid = threadIdx.x, warp = tid >> 5, lane = tid & 31;
    const int cx = blockIdx.x, kh = blockIdx.y;
    const int m0 = blockIdx.z * 128, n0 = cx * 128, k0 = kh * (F_ / 2);
    if (tid == 0) {
        for (int s = 0; s < STAGES; ++s) { mbar_init(full0 + 8 * s, 1); mbar_init(empty0 + 8 * s, 2 * 4); }
        asm volatile("fence.mbarrier_init.release.cluster;" ::: "memory");
    }
    cluster_sync_all();
    float acc[64];
    const int wg = warp >> 2;
    if (warp == 8) {
        if (lane == 0) {
            const uint16_t maskA = (uint16_t)(0xF << (4 * kh));
            for (int k = 0; k < KSTEPS; ++k) {
                const int s = k % STAGES;
                if (k >= STAGES) mbar_wait(empty0 + 8 * s, ((k / STAGES) - 1) & 1);
                mbar_expect_tx(full0 + 8 * s, STAGE_BYTES);
                const uint32_t sa = sbase + s * STAGE_BYTES;
                tma_load_2d_mc(sa + cx * 32 * 128, &mapA, k0 + k * 64, m0 + cx * 32, full0 + 8 * s, maskA);
                tma_load_2d(sa + A_BYTES, &mapB, n0, k0 + k * 64, full0 + 8 * s);
                tma_load_2d(sa + A_BYTES + 8192, &mapB, n0 + 64, k0 + k * 64, full0 + 8 * s);
            }
        }
    } else if (warp < 8) {
        const uint32_t rem_empty0 = mapa(empty0, (lane & 3) + 4 * kh);
#pragma unroll
        for (int i = 0; i < 64; ++i) acc[i] = 0.f;
        for (int k = 0; k < KSTEPS; ++k) {
            const int s = k % STAGES;
            mbar_wait(full0 + 8 * s, (k / STAGES) & 1);
            const uint32_t sa = sbase + s * STAGE_BYTES + wg * 64 * 128;
            const uint32_t sb = sbase + s * STAGE_BYTES + A_BYTES;
            wgmma_fence();
#pragma unroll
            for (int kk = 0; kk < 4; ++kk)
                wgmma_n128(acc, make_desc(sa + kk * 32, 16, 1024, 1), make_desc(sb + kk * 2048, 8192, 1024, 1));
            wgmma_commit();
            if (k > 0) {
                wgmma_wait<1>();
                if ((warp & 3) == 0 && lane < 4) mbar_arrive_cluster(rem_empty0 + 8 * ((k - 1) % STAGES));
            }
        }
        wgmma_wait<0>();
        if (wg != kh) {
            const uint32_t dst = mapa(xbuf, cx + 4 * (kh ^ 1)) + (tid & 127) * 16;
#pragma unroll
            for (int i = 0; i < 16; ++i)
                asm volatile("st.shared::cluster.v4.f32 [%0], {%1,%2,%3,%4};" ::"r"(dst + i * 2048), "f"(acc[4 * i]),
                             "f"(acc[4 * i + 1]), "f"(acc[4 * i + 2]), "f"(acc[4 * i + 3]) : "memory");
        }
    }
    cluster_sync_all();
    if (warp < 8 && wg == kh) {
        const uint32_t src = xbuf + (tid & 127) * 16;
#pragma unroll
        for (int i = 0; i < 16; ++i) {
            float4 v;
            asm volatile("ld.shared.v4.f32 {%0,%1,%2,%3}, [%4];" : "=f"(v.x), "=f"(v.y), "=f"(v.z), "=f"(v.w) : "r"(src + i * 2048));
            acc[4 * i] += v.x; acc[4 * i + 1] += v.y; acc[4 * i + 2] += v.z; acc[4 * i + 3] += v.w;
        }
        const int row0 = m0 + wg * 64 + (warp & 3) * 16 + (lane >> 2);
#pragma unroll
        for (int j = 0; j < 16; ++j) {
            const int col = n0 + j * 8 + (lane & 3) * 2;
            const __nv_bfloat162 bv = *reinterpret_cast<const __nv_bfloat162*>(bias + col);
            const float bb0 = __bfloat162float(bv.x), bb1 = __bfloat162float(bv.y);
#pragma unroll
            for (int hh = 0; hh < 2; ++hh) {
                const int row = row0 + hh * 8;
                const float v0 = bfr(bfr(acc[j * 4 + hh * 2]) + bb0);
                const float v1 = bfr(bfr(acc[j * 4 + hh * 2 + 1]) + bb1);
                const float g0 = bfr(v0 / (1.f + __expf(-v0)));
                const float g1 = bfr(v1 / (1.f + __expf(-v1)));
                const __nv_bfloat162 sv = *reinterpret_cast<const __nv_bfloat162*>(g_s + (size_t)row * D_ + col);
                const __nv_bfloat162 xv = *reinterpret_cast<const __nv_bfloat162*>(xin + (size_t)row * D_ + col);
                const float o0 = __bfloat162float(xv.x) + bfr(__bfloat162float(sv.x) * g0);
                const float o1 = __bfloat162float(xv.y) + bfr(__bfloat162float(sv.y) * g1);
                *reinterpret_cast<uint32_t*>(out + (size_t)row * D_ + col) = pack_bf16(o0, o1);
            }
        }
    }
}

typedef CUresult (*PFN_encodeTiled)(CUtensorMap*, CUtensorMapDataType, cuuint32_t, void*, const cuuint64_t*,
                                    const cuuint64_t*, const cuuint32_t*, const cuuint32_t*, CUtensorMapInterleave,
                                    CUtensorMapSwizzle, CUtensorMapL2promotion, CUtensorMapFloatOOBfill);

static void make_map(PFN_encodeTiled enc, CUtensorMap* m, const void* ptr, uint64_t inner, uint64_t outer,
                     uint32_t box_inner, uint32_t box_outer, CUtensorMapSwizzle swz) {
    cuuint64_t dims[2] = {inner, outer};
    cuuint64_t strides[1] = {inner * 2};
    cuuint32_t box[2] = {box_inner, box_outer};
    cuuint32_t es[2] = {1, 1};
    enc(m, CU_TENSOR_MAP_DATA_TYPE_BFLOAT16, 2, const_cast<void*>(ptr), dims, strides, box, es,
        CU_TENSOR_MAP_INTERLEAVE_NONE, swz, CU_TENSOR_MAP_L2_PROMOTION_L2_256B, CU_TENSOR_MAP_FLOAT_OOB_FILL_NONE);
}

template <typename... KArgs, typename... Args>
static void launch_cluster(void (*k)(KArgs...), dim3 grid, dim3 block, int smem, dim3 cluster, Args... args) {
    cudaLaunchConfig_t cfg = {};
    cfg.gridDim = grid;
    cfg.blockDim = block;
    cfg.dynamicSmemBytes = smem;
    cfg.stream = cudaStreamPerThread;
    cudaLaunchAttribute at[1];
    at[0].id = cudaLaunchAttributeClusterDimension;
    at[0].val.clusterDim.x = cluster.x;
    at[0].val.clusterDim.y = cluster.y;
    at[0].val.clusterDim.z = cluster.z;
    cfg.attrs = at;
    cfg.numAttrs = 1;
    cudaLaunchKernelEx(&cfg, k, KArgs(args)...);
}

extern "C" void kernel_launch(void* const* d_in, const int* in_sizes, int n_in, void* d_out, int out_size) {
    const bf16* x = (const bf16*)d_in[0];
    const bf16* log_A_real = (const bf16*)d_in[1];
    const bf16* A_imag = (const bf16*)d_in[2];
    const bf16* C_real = (const bf16*)d_in[3];
    const bf16* C_imag = (const bf16*)d_in[4];
    const bf16* log_dt = (const bf16*)d_in[5];
    const bf16* D_skip = (const bf16*)d_in[6];
    const bf16* w1 = (const bf16*)d_in[8];
    const bf16* b1 = (const bf16*)d_in[9];
    const bf16* w2 = (const bf16*)d_in[10];
    const bf16* b2 = (const bf16*)d_in[11];
    bf16* out = (bf16*)d_out;

    constexpr int G1_CM = 2, G1_CN = 2, G1_ST = 4, G2_ST = 6;
    constexpr int G1_SMEM = G1_ST * (128 * 64 * 2 + 64 * 224 * 2) + 1024;
    constexpr int G2_SMEM = G2_ST * (128 * 64 * 2 + 64 * 128 * 2) + 32768 + 1024;

    static bool init = false;
    static CUtensorMap mA1, mB1, mA2, mB2;
    if (!init) {
        void* fn = nullptr;
        void *p_xn, *p_h;
        cudaDriverEntryPointQueryResult qr;
        cudaGetDriverEntryPoint("cuTensorMapEncodeTiled", &fn, cudaEnableDefault, &qr);
        PFN_encodeTiled enc = (PFN_encodeTiled)fn;
        cudaGetSymbolAddress(&p_xn, g_xn);
        cudaGetSymbolAddress(&p_h, g_h);
        make_map(enc, &mA1, p_xn, D_, L_, 64, 128 / G1_CN, CU_TENSOR_MAP_SWIZZLE_128B);
        make_map(enc, &mB1, w1, F_, D_, 32, 64 / G1_CM, CU_TENSOR_MAP_SWIZZLE_64B);
        make_map(enc, &mA2, p_h, F_, L_, 64, 32, CU_TENSOR_MAP_SWIZZLE_128B);
        make_map(enc, &mB2, w2, D_, F_, 64, 64, CU_TENSOR_MAP_SWIZZLE_128B);
        cudaFuncSetAttribute(k2_conv, cudaFuncAttributeMaxDynamicSharedMemorySize, CV_SMEM);
        cudaFuncSetAttribute(k_g1<G1_CM, G1_CN, G1_ST>, cudaFuncAttributeMaxDynamicSharedMemorySize, G1_SMEM);
        cudaFuncSetAttribute(k_g2<G2_ST>, cudaFuncAttributeMaxDynamicSharedMemorySize, G2_SMEM);
        init = true;
    }
    k1_prep<<<128, 256>>>(x, log_A_real, A_imag, C_real, C_imag, log_dt);
    k2_conv<<<D_ / CV_CH, 256, CV_SMEM>>>(D_skip);
    launch_cluster(k_g1<G1_CM, G1_CN, G1_ST>, dim3(8, 16), dim3(384), G1_SMEM, dim3(G1_CN, G1_CM, 1), mA1, mB1, b1);
    launch_cluster(k_g2<G2_ST>, dim3(4, 2, 16), dim3(384), G2_SMEM, dim3(4, 2, 1), mA2, mB2, b2, x, out);
}
```

```cpp
#include <cuda_runtime.h>
#include <cuda_bf16.h>
#include <cuda.h>
#include <stdint.h>

typedef __nv_bfloat16 bf16;

constexpr int L_ = 2048, D_ = 512, N_ = 128, F_ = 1792;

__device__ __align__(1024) bf16 g_xn[L_ * D_];
__device__ __align__(1024) bf16 g_xnT[D_ * L_];
__device__ __align__(1024) bf16 g_K[D_ * L_];
__device__ __align__(1024) bf16 g_s[L_ * D_];
__device__ __align__(1024) bf16 g_h[L_ * F_];

__device__ __forceinline__ float bfr(float x) { return __bfloat162float(__float2bfloat16(x)); }
__device__ __forceinline__ uint32_t smem_u32(const void* p) { return (uint32_t)__cvta_generic_to_shared(p); }
__device__ __forceinline__ uint32_t pack_bf16(float lo, float hi) {
    __nv_bfloat162 v = __floats2bfloat162_rn(lo, hi);
    return *reinterpret_cast<uint32_t*>(&v);
}

__device__ __forceinline__ void mbar_init(uint32_t bar, uint32_t count) {
    asm volatile("mbarrier.init.shared::cta.b64 [%0], %1;" ::"r"(bar), "r"(count) : "memory");
}
__device__ __forceinline__ void mbar_expect_tx(uint32_t bar, uint32_t bytes) {
    asm volatile("mbarrier.arrive.expect_tx.shared::cta.b64 _, [%0], %1;" ::"r"(bar), "r"(bytes) : "memory");
}
__device__ __forceinline__ void mbar_arrive(uint32_t bar) {
    asm volatile("mbarrier.arrive.shared::cta.b64 _, [%0];" ::"r"(bar) : "memory");
}
__device__ __forceinline__ void mbar_wait(uint32_t bar, uint32_t parity) {
    uint32_t done;
    int it = 0;
    do {
        asm volatile(
            "{\n.reg .pred p;\n"
            "mbarrier.try_wait.parity.shared::cta.b64 p, [%1], %2;\n"
            "selp.u32 %0, 1, 0, p;\n}\n"
            : "=r"(done) : "r"(bar), "r"(parity) : "memory");
    } while (!done && ++it < (1 << 26));
}
__device__ __forceinline__ void tma_load_2d(uint32_t smem, const CUtensorMap* map, int c0, int c1, uint32_t bar) {
    asm volatile(
        "cp.async.bulk.tensor.2d.shared::cluster.global.mbarrier::complete_tx::bytes [%0], [%1, {%3, %4}], [%2];"
        ::"r"(smem), "l"(reinterpret_cast<uint64_t>(map)), "r"(bar), "r"(c0), "r"(c1) : "memory");
}
__device__ __forceinline__ void tma_load_2d_mc(uint32_t smem, const CUtensorMap* map, int c0, int c1, uint32_t bar,
                                               uint16_t mask) {
    asm volatile(
        "cp.async.bulk.tensor.2d.shared::cluster.global.mbarrier::complete_tx::bytes.multicast::cluster [%0], [%1, {%3, %4}], [%2], %5;"
        ::"r"(smem), "l"(reinterpret_cast<uint64_t>(map)), "r"(bar), "r"(c0), "r"(c1), "h"(mask) : "memory");
}
__device__ __forceinline__ uint32_t mapa(uint32_t addr, uint32_t cta) {
    uint32_t r;
    asm volatile("mapa.shared::cluster.u32 %0, %1, %2;" : "=r"(r) : "r"(addr), "r"(cta));
    return r;
}
__device__ __forceinline__ void mbar_arrive_cluster(uint32_t cluster_addr) {
    asm volatile("mbarrier.arrive.release.cluster.shared::cluster.b64 _, [%0];" ::"r"(cluster_addr) : "memory");
}
__device__ __forceinline__ void cluster_sync_all() {
    asm volatile("barrier.cluster.arrive.release.aligned;\nbarrier.cluster.wait.acquire.aligned;" ::: "memory");
}
__device__ __forceinline__ void wgmma_fence() { asm volatile("wgmma.fence.sync.aligned;" ::: "memory"); }
__device__ __forceinline__ void wgmma_commit() { asm volatile("wgmma.commit_group.sync.aligned;" ::: "memory"); }
template <int N> __device__ __forceinline__ void wgmma_wait() {
    asm volatile("wgmma.wait_group.sync.aligned %0;" ::"n"(N) : "memory");
}
__device__ __forceinline__ uint64_t make_desc(uint32_t addr, uint32_t lbo_bytes, uint32_t sbo_bytes, uint32_t swz = 1) {
    uint64_t d = 0;
    d |= (uint64_t)((addr & 0x3FFFF) >> 4);
    d |= (uint64_t)((lbo_bytes >> 4) & 0x3FFF) << 16;
    d |= (uint64_t)((sbo_bytes >> 4) & 0x3FFF) << 32;
    d |= (uint64_t)swz << 62;
    return d;
}

__device__ __forceinline__ void wgmma_n128(float (&d)[64], uint64_t da, uint64_t db) {
    asm volatile(
        "wgmma.mma_async.sync.aligned.m64n128k16.f32.bf16.bf16 {%0,%1,%2,%3,%4,%5,%6,%7,%8,%9,%10,%11,%12,%13,%14,%15,%16,%17,%18,%19,%20,%21,%22,%23,%24,%25,%26,%27,%28,%29,%30,%31,%32,%33,%34,%35,%36,%37,%38,%39,%40,%41,%42,%43,%44,%45,%46,%47,%48,%49,%50,%51,%52,%53,%54,%55,%56,%57,%58,%59,%60,%61,%62,%63}, %64, %65, 1, 1, 1, 0, 1;\n"
        : "+f"(d[0]), "+f"(d[1]), "+f"(d[2]), "+f"(d[3]), "+f"(d[4]), "+f"(d[5]), "+f"(d[6]), "+f"(d[7]), "+f"(d[8]), "+f"(d[9]), "+f"(d[10]), "+f"(d[11]), "+f"(d[12]), "+f"(d[13]), "+f"(d[14]), "+f"(d[15]), "+f"(d[16]), "+f"(d[17]), "+f"(d[18]), "+f"(d[19]), "+f"(d[20]), "+f"(d[21]), "+f"(d[22]), "+f"(d[23]), "+f"(d[24]), "+f"(d[25]), "+f"(d[26]), "+f"(d[27]), "+f"(d[28]), "+f"(d[29]), "+f"(d[30]), "+f"(d[31]), "+f"(d[32]), "+f"(d[33]), "+f"(d[34]), "+f"(d[35]), "+f"(d[36]), "+f"(d[37]), "+f"(d[38]), "+f"(d[39]), "+f"(d[40]), "+f"(d[41]), "+f"(d[42]), "+f"(d[43]), "+f"(d[44]), "+f"(d[45]), "+f"(d[46]), "+f"(d[47]), "+f"(d[48]), "+f"(d[49]), "+f"(d[50]), "+f"(d[51]), "+f"(d[52]), "+f"(d[53]), "+f"(d[54]), "+f"(d[55]), "+f"(d[56]), "+f"(d[57]), "+f"(d[58]), "+f"(d[59]), "+f"(d[60]), "+f"(d[61]), "+f"(d[62]), "+f"(d[63])
        : "l"(da), "l"(db));
}

__device__ __forceinline__ void wgmma_n256(float (&d)[128], uint64_t da, uint64_t db) {
    asm volatile(
        "wgmma.mma_async.sync.aligned.m64n256k16.f32.bf16.bf16 {%0,%1,%2,%3,%4,%5,%6,%7,%8,%9,%10,%11,%12,%13,%14,%15,%16,%17,%18,%19,%20,%21,%22,%23,%24,%25,%26,%27,%28,%29,%30,%31,%32,%33,%34,%35,%36,%37,%38,%39,%40,%41,%42,%43,%44,%45,%46,%47,%48,%49,%50,%51,%52,%53,%54,%55,%56,%57,%58,%59,%60,%61,%62,%63,%64,%65,%66,%67,%68,%69,%70,%71,%72,%73,%74,%75,%76,%77,%78,%79,%80,%81,%82,%83,%84,%85,%86,%87,%88,%89,%90,%91,%92,%93,%94,%95,%96,%97,%98,%99,%100,%101,%102,%103,%104,%105,%106,%107,%108,%109,%110,%111,%112,%113,%114,%115,%116,%117,%118,%119,%120,%121,%122,%123,%124,%125,%126,%127}, %128, %129, 1, 1, 1, 0, 1;\n"
        : "+f"(d[0]), "+f"(d[1]), "+f"(d[2]), "+f"(d[3]), "+f"(d[4]), "+f"(d[5]), "+f"(d[6]), "+f"(d[7]), "+f"(d[8]), "+f"(d[9]), "+f"(d[10]), "+f"(d[11]), "+f"(d[12]), "+f"(d[13]), "+f"(d[14]), "+f"(d[15]), "+f"(d[16]), "+f"(d[17]), "+f"(d[18]), "+f"(d[19]), "+f"(d[20]), "+f"(d[21]), "+f"(d[22]), "+f"(d[23]), "+f"(d[24]), "+f"(d[25]), "+f"(d[26]), "+f"(d[27]), "+f"(d[28]), "+f"(d[29]), "+f"(d[30]), "+f"(d[31]), "+f"(d[32]), "+f"(d[33]), "+f"(d[34]), "+f"(d[35]), "+f"(d[36]), "+f"(d[37]), "+f"(d[38]), "+f"(d[39]), "+f"(d[40]), "+f"(d[41]), "+f"(d[42]), "+f"(d[43]), "+f"(d[44]), "+f"(d[45]), "+f"(d[46]), "+f"(d[47]), "+f"(d[48]), "+f"(d[49]), "+f"(d[50]), "+f"(d[51]), "+f"(d[52]), "+f"(d[53]), "+f"(d[54]), "+f"(d[55]), "+f"(d[56]), "+f"(d[57]), "+f"(d[58]), "+f"(d[59]), "+f"(d[60]), "+f"(d[61]), "+f"(d[62]), "+f"(d[63]), "+f"(d[64]), "+f"(d[65]), "+f"(d[66]), "+f"(d[67]), "+f"(d[68]), "+f"(d[69]), "+f"(d[70]), "+f"(d[71]), "+f"(d[72]), "+f"(d[73]), "+f"(d[74]), "+f"(d[75]), "+f"(d[76]), "+f"(d[77]), "+f"(d[78]), "+f"(d[79]), "+f"(d[80]), "+f"(d[81]), "+f"(d[82]), "+f"(d[83]), "+f"(d[84]), "+f"(d[85]), "+f"(d[86]), "+f"(d[87]), "+f"(d[88]), "+f"(d[89]), "+f"(d[90]), "+f"(d[91]), "+f"(d[92]), "+f"(d[93]), "+f"(d[94]), "+f"(d[95]), "+f"(d[96]), "+f"(d[97]), "+f"(d[98]), "+f"(d[99]), "+f"(d[100]), "+f"(d[101]), "+f"(d[102]), "+f"(d[103]), "+f"(d[104]), "+f"(d[105]), "+f"(d[106]), "+f"(d[107]), "+f"(d[108]), "+f"(d[109]), "+f"(d[110]), "+f"(d[111]), "+f"(d[112]), "+f"(d[113]), "+f"(d[114]), "+f"(d[115]), "+f"(d[116]), "+f"(d[117]), "+f"(d[118]), "+f"(d[119]), "+f"(d[120]), "+f"(d[121]), "+f"(d[122]), "+f"(d[123]), "+f"(d[124]), "+f"(d[125]), "+f"(d[126]), "+f"(d[127])
        : "l"(da), "l"(db));
}


__device__ __forceinline__ void mma_bf16(float (&c)[4], uint32_t a0, uint32_t a1, uint32_t a2, uint32_t a3,
                                         uint32_t b0, uint32_t b1) {
    asm volatile(
        "mma.sync.aligned.m16n8k16.row.col.f32.bf16.bf16.f32 {%0,%1,%2,%3}, {%4,%5,%6,%7}, {%8,%9}, {%0,%1,%2,%3};"
        : "+f"(c[0]), "+f"(c[1]), "+f"(c[2]), "+f"(c[3])
        : "r"(a0), "r"(a1), "r"(a2), "r"(a3), "r"(b0), "r"(b1));
}
__device__ __forceinline__ void mma_tf32(float (&c)[4], uint32_t a0, uint32_t a1, uint32_t a2, uint32_t a3,
                                         uint32_t b0, uint32_t b1) {
    asm volatile(
        "mma.sync.aligned.m16n8k8.row.col.f32.tf32.tf32.f32 {%0,%1,%2,%3}, {%4,%5,%6,%7}, {%8,%9}, {%0,%1,%2,%3};"
        : "+f"(c[0]), "+f"(c[1]), "+f"(c[2]), "+f"(c[3])
        : "r"(a0), "r"(a1), "r"(a2), "r"(a3), "r"(b0), "r"(b1));
}
__device__ __forceinline__ uint32_t to_tf32(float x) {
    uint32_t r;
    asm("cvt.rna.tf32.f32 %0, %1;" : "=r"(r) : "f"(x));
    return r;
}
__device__ __forceinline__ void ldmatrix_x4(uint32_t& r0, uint32_t& r1, uint32_t& r2, uint32_t& r3, uint32_t addr) {
    asm volatile("ldmatrix.sync.aligned.m8n8.x4.shared.b16 {%0,%1,%2,%3}, [%4];"
                 : "=r"(r0), "=r"(r1), "=r"(r2), "=r"(r3) : "r"(addr));
}

struct cplx { float r, i; };
__device__ __forceinline__ cplx cmul(cplx a, cplx b) { return {a.r * b.r - a.i * b.i, a.r * b.i + a.i * b.r}; }
__device__ __forceinline__ cplx csq(cplx a) { return {a.r * a.r - a.i * a.i, 2.f * a.r * a.i}; }
__device__ __forceinline__ cplx cexp_(float ar, float ai) {
    float m = expf(ar), s, c;
    sincosf(ai, &s, &c);
    return {m * c, m * s};
}

__global__ void __launch_bounds__(256) k1_prep(const bf16* __restrict__ x, const bf16* __restrict__ log_A_real,
                                               const bf16* __restrict__ A_imag, const bf16* __restrict__ C_real,
                                               const bf16* __restrict__ C_imag, const bf16* __restrict__ log_dt) {
    __shared__ __align__(16) unsigned char smraw[32 * 520 * 2];
    const int warp = threadIdx.x >> 5, lane = threadIdx.x & 31;
    if (blockIdx.x < 64) {
        bf16* tile = reinterpret_cast<bf16*>(smraw);
        const int l0 = blockIdx.x * 32;
        for (int rr = 0; rr < 4; ++rr) {
            const int r = warp * 4 + rr;
            const bf16* row = x + (size_t)(l0 + r) * D_;
            uint4 v0 = *reinterpret_cast<const uint4*>(row + lane * 8);
            uint4 v1 = *reinterpret_cast<const uint4*>(row + 256 + lane * 8);
            float f[16];
            const bf16* p0 = reinterpret_cast<const bf16*>(&v0);
            const bf16* p1 = reinterpret_cast<const bf16*>(&v1);
#pragma unroll
            for (int i = 0; i < 8; ++i) { f[i] = __bfloat162float(p0[i]); f[8 + i] = __bfloat162float(p1[i]); }
            float sum = 0.f;
#pragma unroll
            for (int i = 0; i < 16; ++i) sum += f[i];
#pragma unroll
            for (int o = 16; o; o >>= 1) sum += __shfl_xor_sync(0xffffffffu, sum, o);
            const float mean = sum * (1.f / D_);
            float vs = 0.f;
#pragma unroll
            for (int i = 0; i < 16; ++i) { float d = f[i] - mean; vs += d * d; }
#pragma unroll
            for (int o = 16; o; o >>= 1) vs += __shfl_xor_sync(0xffffffffu, vs, o);
            const float m_b = bfr(mean);
            const float v_b = bfr(vs * (1.f / D_));
            const float den = bfr(sqrtf(bfr(v_b + 1e-5f)));
            uint4 o0, o1;
            bf16* q0 = reinterpret_cast<bf16*>(&o0);
            bf16* q1 = reinterpret_cast<bf16*>(&o1);
#pragma unroll
            for (int i = 0; i < 8; ++i) {
                q0[i] = __float2bfloat16(bfr(f[i] - m_b) / den);
                q1[i] = __float2bfloat16(bfr(f[8 + i] - m_b) / den);
            }
            *reinterpret_cast<uint4*>(g_xn + (size_t)(l0 + r) * D_ + lane * 8) = o0;
            *reinterpret_cast<uint4*>(g_xn + (size_t)(l0 + r) * D_ + 256 + lane * 8) = o1;
            *reinterpret_cast<uint4*>(tile + r * 520 + lane * 8) = o0;
            *reinterpret_cast<uint4*>(tile + r * 520 + 256 + lane * 8) = o1;
        }
        __syncthreads();
        for (int c = threadIdx.x; c < D_; c += 256) {
            uint32_t w[16];
#pragma unroll
            for (int i = 0; i < 16; ++i) {
                uint32_t lo = *reinterpret_cast<const unsigned short*>(tile + (2 * i) * 520 + c);
                uint32_t hi = *reinterpret_cast<const unsigned short*>(tile + (2 * i + 1) * 520 + c);
                w[i] = lo | (hi << 16);
            }
            uint4* dst = reinterpret_cast<uint4*>(g_xnT + (size_t)c * L_ + l0);
#pragma unroll
            for (int i = 0; i < 4; ++i) dst[i] = make_uint4(w[4 * i], w[4 * i + 1], w[4 * i + 2], w[4 * i + 3]);
        }
    } else {
        float* Kd = reinterpret_cast<float*>(smraw) + warp * 648;
        const int c = (blockIdx.x - 64) * 8 + warp;
        const int g = lane >> 2, t = lane & 3;
        const float dt = bfr(expf(__bfloat162float(log_dt[c])));
        float acc[5][4];
#pragma unroll
        for (int s = 0; s < 5; ++s)
#pragma unroll
            for (int i = 0; i < 4; ++i) acc[s][i] = 0.f;
        float k2048 = 0.f;
        for (int ks = 0; ks < 32; ++ks) {
            const int m = c * N_ + ks * 4 + t;
            const float ar = -bfr(expf(__bfloat162float(log_A_real[m]))) * dt;
            const float ai = __bfloat162float(A_imag[m]) * dt;
            const cplx C = {__bfloat162float(C_real[m]) * dt, __bfloat162float(C_imag[m]) * dt};
            const cplx q1 = cexp_(ar * (float)g, ai * (float)g);
            const cplx w8 = cexp_(ar * 8.f, ai * 8.f);
            const cplx q2 = csq(q1), q4 = csq(q2), q8 = csq(q4), q16 = csq(q8), q32 = csq(q16), q64 = csq(q32);
            const cplx c16 = csq(w8), c32 = csq(c16), c64 = csq(c32), c128 = csq(c64), c256 = csq(c128),
                       c512 = csq(c256), c1024 = csq(c512);
            cplx lo, hi;
            lo = cmul(C, q8); hi = cmul(lo, c64);
            mma_tf32(acc[0], to_tf32(lo.r), to_tf32(hi.r), to_tf32(-lo.i), to_tf32(-hi.i), to_tf32(q1.r), to_tf32(q1.i));
            lo = cmul(lo, c128); hi = cmul(lo, c64);
            mma_tf32(acc[1], to_tf32(lo.r), to_tf32(hi.r), to_tf32(-lo.i), to_tf32(-hi.i), to_tf32(q1.r), to_tf32(q1.i));
            lo = cmul(cmul(C, q16), c256); hi = cmul(lo, c128);
            mma_tf32(acc[2], to_tf32(lo.r), to_tf32(hi.r), to_tf32(-lo.i), to_tf32(-hi.i), to_tf32(q2.r), to_tf32(q2.i));
            lo = cmul(cmul(C, q32), c512); hi = cmul(lo, c256);
            mma_tf32(acc[3], to_tf32(lo.r), to_tf32(hi.r), to_tf32(-lo.i), to_tf32(-hi.i), to_tf32(q4.r), to_tf32(q4.i));
            lo = cmul(cmul(C, q64), c1024); hi = cmul(lo, c512);
            mma_tf32(acc[4], to_tf32(lo.r), to_tf32(hi.r), to_tf32(-lo.i), to_tf32(-hi.i), to_tf32(q8.r), to_tf32(q8.i));
            if (g == 0) { cplx e = cmul(C, csq(c1024)); k2048 += e.r; }
        }
        k2048 += __shfl_xor_sync(0xffffffffu, k2048, 1);
        k2048 += __shfl_xor_sync(0xffffffffu, k2048, 2);
#pragma unroll
        for (int s = 0; s < 5; ++s) {
            Kd[s * 128 + 8 * g + 2 * t] = 2.f * acc[s][0];
            Kd[s * 128 + 8 * g + 2 * t + 1] = 2.f * acc[s][1];
            Kd[s * 128 + 8 * (g + 8) + 2 * t] = 2.f * acc[s][2];
            Kd[s * 128 + 8 * (g + 8) + 2 * t + 1] = 2.f * acc[s][3];
        }
        if (lane == 0) Kd[640] = 2.f * k2048;
        __syncwarp();
        for (int l2 = lane; l2 < L_ / 2; l2 += 32) {
            float v[2];
#pragma unroll
            for (int e = 0; e < 2; ++e) {
                const int l = 2 * l2 + e;
                const int p = (int)bfr((float)l);
                int idx;
                if (p < 256) idx = p;
                else if (p < 512) idx = 256 + ((p - 256) >> 1);
                else if (p < 1024) idx = 384 + ((p - 512) >> 2);
                else if (p < 2048) idx = 512 + ((p - 1024) >> 3);
                else idx = 640;
                v[e] = Kd[idx];
            }
            reinterpret_cast<uint32_t*>(g_K + (size_t)c * L_)[l2] = pack_bf16(v[0], v[1]);
        }
    }
}

constexpr int CV_PKPAD = 64;
constexpr int CV_PK = CV_PKPAD + L_ + 16;
constexpr int CV_UROWS = 40;
constexpr int CV_UPITCH = 72;
constexpr int CV_CH = 4;
constexpr int CV_SMEM = CV_CH * (CV_PK * 4 + CV_UROWS * CV_UPITCH * 2);

__global__ void __launch_bounds__(256) k2_conv(const bf16* __restrict__ D_skip) {
    extern __shared__ __align__(16) unsigned char sm[];
    uint32_t* PKall = reinterpret_cast<uint32_t*>(sm);
    bf16* Uall = reinterpret_cast<bf16*>(sm + CV_CH * CV_PK * 4);
    const int c0 = blockIdx.x * CV_CH;
    const int tid = threadIdx.x, warp = tid >> 5, lane = tid & 31;
    for (int ch = 0; ch < CV_CH; ++ch) {
        uint32_t* PK = PKall + ch * CV_PK;
        bf16* U = Uall + ch * CV_UROWS * CV_UPITCH;
        const unsigned short* Kg = reinterpret_cast<const unsigned short*>(g_K + (size_t)(c0 + ch) * L_);
        for (int i = tid; i < CV_PK; i += 256) {
            const int idx = i - CV_PKPAD;
            uint32_t lo = (idx >= 0 && idx < L_) ? Kg[idx] : 0;
            uint32_t hi = (idx - 1 >= 0 && idx - 1 < L_) ? Kg[idx - 1] : 0;
            PK[i] = lo | (hi << 16);
        }
        for (int i = tid; i < 8 * CV_UPITCH / 2; i += 256) reinterpret_cast<uint32_t*>(U)[i] = 0;
        const uint4* src = reinterpret_cast<const uint4*>(g_xnT + (size_t)(c0 + ch) * L_);
        for (int i = tid; i < L_ / 8; i += 256) {
            const int a = i >> 3, b8 = i & 7;
            *reinterpret_cast<uint4*>(U + (a + 8) * CV_UPITCH + b8 * 8) = src[i];
        }
    }
    __syncthreads();
    const int ch = warp >> 1, half = warp & 1;
    const int g = lane >> 2, t = lane & 3;
    const uint32_t* PK = PKall + ch * CV_PK + CV_PKPAD + (g - 2 * t);
    const uint32_t ubase = smem_u32(Uall + ch * CV_UROWS * CV_UPITCH);
    float acc[2][4][4];
#pragma unroll
    for (int i = 0; i < 2; ++i)
#pragma unroll
        for (int n = 0; n < 4; ++n)
#pragma unroll
            for (int q = 0; q < 4; ++q) acc[i][n][q] = 0.f;
    const int lm_row = lane & 7, lm_kh = (lane >> 3) & 1, lm_nt = lane >> 4;
#pragma unroll
    for (int d1 = 0; d1 < 4; ++d1) {
#pragma unroll 1
        for (int d0 = 0; d0 < 8; ++d0) {
            const int delta = d1 * 8 + d0;
            uint32_t W[11];
#pragma unroll
            for (int j = 0; j < 11; ++j) W[j] = PK[8 * (8 * delta + 4 * half - 7 + j)];
#pragma unroll
            for (int kb = 0; kb < 4; ++kb) {
#pragma unroll
                for (int np = 0; np < 2; ++np) {
                    if (2 * np + 1 < d1) continue;
                    uint32_t b[4];
                    const int col = 8 * (2 * np + lm_nt) + lm_row - delta + 8;
                    const uint32_t addr = ubase + (uint32_t)(col * CV_UPITCH + kb * 16 + lm_kh * 8) * 2;
                    ldmatrix_x4(b[0], b[1], b[2], b[3], addr);
#pragma unroll
                    for (int i = 0; i < 2; ++i) {
                        const int w = 2 * (i - kb) + 6;
                        const uint32_t a0 = W[w + 1], a1 = W[w + 2], a2 = W[w], a3 = W[w + 1];
                        if (2 * np >= d1) mma_bf16(acc[i][2 * np], a0, a1, a2, a3, b[0], b[1]);
                        mma_bf16(acc[i][2 * np + 1], a0, a1, a2, a3, b[2], b[3]);
                    }
                }
            }
        }
    }
    __syncthreads();
    bf16* Ys = reinterpret_cast<bf16*>(sm);
#pragma unroll
    for (int i = 0; i < 2; ++i)
#pragma unroll
        for (int n = 0; n < 4; ++n) {
            const int b = (2 * half + i) * 16 + g;
            const int a = n * 8 + 2 * t;
            Ys[(64 * a + b) * 4 + ch] = __float2bfloat16(acc[i][n][0]);
            Ys[(64 * (a + 1) + b) * 4 + ch] = __float2bfloat16(acc[i][n][1]);
            Ys[(64 * a + b + 8) * 4 + ch] = __float2bfloat16(acc[i][n][2]);
            Ys[(64 * (a + 1) + b + 8) * 4 + ch] = __float2bfloat16(acc[i][n][3]);
        }
    __syncthreads();
    float dsk[4];
#pragma unroll
    for (int q = 0; q < 4; ++q) dsk[q] = __bfloat162float(D_skip[c0 + q]);
    for (int l = tid; l < L_; l += 256) {
        uint2 yv = *reinterpret_cast<const uint2*>(Ys + l * 4);
        uint2 xv = *reinterpret_cast<const uint2*>(g_xn + (size_t)l * D_ + c0);
        const bf16* yp = reinterpret_cast<const bf16*>(&yv);
        const bf16* xp = reinterpret_cast<const bf16*>(&xv);
        uint2 o;
        bf16* op = reinterpret_cast<bf16*>(&o);
#pragma unroll
        for (int q = 0; q < 4; ++q)
            op[q] = __float2bfloat16(__bfloat162float(yp[q]) + bfr(__bfloat162float(xp[q]) * dsk[q]));
        *reinterpret_cast<uint2*>(g_s + (size_t)l * D_ + c0) = o;
    }
}

template <int BN, int KSTEPS, int CM, int CN, int STAGES>
struct Gemm {
    static constexpr int A_BYTES = 128 * 64 * 2;
    static constexpr int B_BYTES = 64 * BN * 2;
    static constexpr int STAGE_BYTES = A_BYTES + B_BYTES;
    static constexpr int NSRC = CM + CN - 1;
    static constexpr int SMEM = STAGES * STAGE_BYTES + 1024;

    __device__ static __forceinline__ void init_bars(uint32_t full0, uint32_t empty0) {
        for (int s = 0; s < STAGES; ++s) { mbar_init(full0 + 8 * s, 1); mbar_init(empty0 + 8 * s, 2 * NSRC); }
        asm volatile("fence.mbarrier_init.release.cluster;" ::: "memory");
    }
    __device__ static __forceinline__ void produce(const CUtensorMap* mapA, const CUtensorMap* mapB, uint32_t sbase,
                                                   uint32_t full0, uint32_t empty0, int m0, int n0, int cx, int cy) {
        uint16_t maskA = 0, maskB = 0;
        for (int i = 0; i < CN; ++i) maskA |= 1 << (i + CN * cy);
        for (int i = 0; i < CM; ++i) maskB |= 1 << (cx + CN * i);
        for (int k = 0; k < KSTEPS; ++k) {
            const int s = k % STAGES;
            if (k >= STAGES) mbar_wait(empty0 + 8 * s, ((k / STAGES) - 1) & 1);
            mbar_expect_tx(full0 + 8 * s, STAGE_BYTES);
            const uint32_t sa = sbase + s * STAGE_BYTES;
            tma_load_2d_mc(sa + cx * (128 / CN) * 128, mapA, k * 64, m0 + cx * (128 / CN), full0 + 8 * s, maskA);
#pragma unroll
            for (int j = 0; j < BN / 64; ++j)
                tma_load_2d_mc(sa + A_BYTES + j * 8192 + cy * (64 / CM) * 128, mapB, n0 + j * 64,
                               k * 64 + cy * (64 / CM), full0 + 8 * s, maskB);
        }
    }
    __device__ static __forceinline__ void consume(float (&acc)[BN / 2], uint32_t sbase, uint32_t full0,
                                                   uint32_t empty0, int cx, int cy) {
        const int warp = threadIdx.x >> 5, lane = threadIdx.x & 31, wg = warp >> 2;
        uint32_t tgt = 0;
        if (lane < CN) tgt = lane + CN * cy;
        else if (lane < NSRC) { int i = lane - CN; if (i >= cy) ++i; tgt = cx + CN * i; }
        const uint32_t rem_empty0 = mapa(empty0, tgt);
#pragma unroll
        for (int i = 0; i < BN / 2; ++i) acc[i] = 0.f;
        for (int k = 0; k < KSTEPS; ++k) {
            const int s = k % STAGES;
            mbar_wait(full0 + 8 * s, (k / STAGES) & 1);
            const uint32_t sa = sbase + s * STAGE_BYTES + wg * 64 * 128;
            const uint32_t sb = sbase + s * STAGE_BYTES + A_BYTES;
            wgmma_fence();
#pragma unroll
            for (int kk = 0; kk < 4; ++kk) {
                if constexpr (BN == 256) wgmma_n256(acc, make_desc(sa + kk * 32, 16, 1024), make_desc(sb + kk * 2048, 8192, 1024));
                else wgmma_n128(acc, make_desc(sa + kk * 32, 16, 1024), make_desc(sb + kk * 2048, 8192, 1024));
            }
            wgmma_commit();
            if (k > 0) {
                wgmma_wait<1>();
                if ((warp & 3) == 0 && lane < NSRC) mbar_arrive_cluster(rem_empty0 + 8 * ((k - 1) % STAGES));
            }
        }
        wgmma_wait<0>();
    }
};

typedef Gemm<256, D_ / 64, 8, 1, 4> G1;
typedef Gemm<128, F_ / 64, 2, 4, 6> G2;

__global__ void __launch_bounds__(384) k_g1(const __grid_constant__ CUtensorMap mapA,
                                            const __grid_constant__ CUtensorMap mapB,
                                            const bf16* __restrict__ bias) {
    extern __shared__ __align__(1024) unsigned char smem_raw[];
    const uint32_t sbase = (smem_u32(smem_raw) + 1023) & ~1023u;
    __shared__ __align__(8) uint64_t bars[16];
    const uint32_t full0 = smem_u32(bars), empty0 = smem_u32(bars + 8);
    const int tid = threadIdx.x, warp = tid >> 5, lane = tid & 31;
    const int m0 = blockIdx.y * 128, n0 = blockIdx.x * 256;
    const int cx = 0, cy = blockIdx.y % 8;
    if (tid == 0) G1::init_bars(full0, empty0);
    cluster_sync_all();
    if (warp == 8) {
        if (lane == 0) G1::produce(&mapA, &mapB, sbase, full0, empty0, m0, n0, cx, cy);
    } else if (warp < 8) {
        float acc[128];
        G1::consume(acc, sbase, full0, empty0, cx, cy);
        const int row0 = m0 + (warp >> 2) * 64 + (warp & 3) * 16 + (lane >> 2);
#pragma unroll
        for (int j = 0; j < 32; ++j) {
            const int col = n0 + j * 8 + (lane & 3) * 2;
            const __nv_bfloat162 bv = *reinterpret_cast<const __nv_bfloat162*>(bias + col);
            const float bb0 = __bfloat162float(bv.x), bb1 = __bfloat162float(bv.y);
#pragma unroll
            for (int hh = 0; hh < 2; ++hh) {
                float v0 = bfr(bfr(acc[j * 4 + hh * 2]) + bb0);
                float v1 = bfr(bfr(acc[j * 4 + hh * 2 + 1]) + bb1);
                v0 = v0 > 0.f ? v0 : 0.f;
                v1 = v1 > 0.f ? v1 : 0.f;
                *reinterpret_cast<uint32_t*>(g_h + (size_t)(row0 + hh * 8) * F_ + col) = pack_bf16(v0 * v0, v1 * v1);
            }
        }
    }
    cluster_sync_all();
}

__global__ void __launch_bounds__(384) k_g2(const __grid_constant__ CUtensorMap mapA,
                                            const __grid_constant__ CUtensorMap mapB,
                                            const bf16* __restrict__ bias, const bf16* __restrict__ xin,
                                            bf16* __restrict__ out) {
    extern __shared__ __align__(1024) unsigned char smem_raw[];
    const uint32_t sbase = (smem_u32(smem_raw) + 1023) & ~1023u;
    __shared__ __align__(8) uint64_t bars[16];
    const uint32_t full0 = smem_u32(bars), empty0 = smem_u32(bars + 8);
    const int tid = threadIdx.x, warp = tid >> 5, lane = tid & 31;
    const int m0 = blockIdx.y * 128, n0 = blockIdx.x * 128;
    const int cx = blockIdx.x, cy = blockIdx.y % 2;
    if (tid == 0) G2::init_bars(full0, empty0);
    cluster_sync_all();
    if (warp == 8) {
        if (lane == 0) G2::produce(&mapA, &mapB, sbase, full0, empty0, m0, n0, cx, cy);
    } else if (warp < 8) {
        float acc[64];
        G2::consume(acc, sbase, full0, empty0, cx, cy);
        const int row0 = m0 + (warp >> 2) * 64 + (warp & 3) * 16 + (lane >> 2);
#pragma unroll
        for (int j = 0; j < 16; ++j) {
            const int col = n0 + j * 8 + (lane & 3) * 2;
            const __nv_bfloat162 bv = *reinterpret_cast<const __nv_bfloat162*>(bias + col);
            const float bb0 = __bfloat162float(bv.x), bb1 = __bfloat162float(bv.y);
#pragma unroll
            for (int hh = 0; hh < 2; ++hh) {
                const int row = row0 + hh * 8;
                const float v0 = bfr(bfr(acc[j * 4 + hh * 2]) + bb0);
                const float v1 = bfr(bfr(acc[j * 4 + hh * 2 + 1]) + bb1);
                const float g0 = bfr(v0 / (1.f + __expf(-v0)));
                const float g1 = bfr(v1 / (1.f + __expf(-v1)));
                const __nv_bfloat162 sv = *reinterpret_cast<const __nv_bfloat162*>(g_s + (size_t)row * D_ + col);
                const __nv_bfloat162 xv = *reinterpret_cast<const __nv_bfloat162*>(xin + (size_t)row * D_ + col);
                const float o0 = __bfloat162float(xv.x) + bfr(__bfloat162float(sv.x) * g0);
                const float o1 = __bfloat162float(xv.y) + bfr(__bfloat162float(sv.y) * g1);
                *reinterpret_cast<uint32_t*>(out + (size_t)row * D_ + col) = pack_bf16(o0, o1);
            }
        }
    }
    cluster_sync_all();
}

typedef CUresult (*PFN_encodeTiled)(CUtensorMap*, CUtensorMapDataType, cuuint32_t, void*, const cuuint64_t*,
                                    const cuuint64_t*, const cuuint32_t*, const cuuint32_t*, CUtensorMapInterleave,
                                    CUtensorMapSwizzle, CUtensorMapL2promotion, CUtensorMapFloatOOBfill);

static void make_map(PFN_encodeTiled enc, CUtensorMap* m, const void* ptr, uint64_t inner, uint64_t outer,
                     uint32_t box_inner, uint32_t box_outer, CUtensorMapSwizzle swz) {
    cuuint64_t dims[2] = {inner, outer};
    cuuint64_t strides[1] = {inner * 2};
    cuuint32_t box[2] = {box_inner, box_outer};
    cuuint32_t es[2] = {1, 1};
    enc(m, CU_TENSOR_MAP_DATA_TYPE_BFLOAT16, 2, const_cast<void*>(ptr), dims, strides, box, es,
        CU_TENSOR_MAP_INTERLEAVE_NONE, swz, CU_TENSOR_MAP_L2_PROMOTION_L2_256B, CU_TENSOR_MAP_FLOAT_OOB_FILL_NONE);
}

template <typename... KArgs, typename... Args>
static void launch_cluster(void (*k)(KArgs...), dim3 grid, dim3 block, int smem, dim3 cluster, Args... args) {
    cudaLaunchConfig_t cfg = {};
    cfg.gridDim = grid;
    cfg.blockDim = block;
    cfg.dynamicSmemBytes = smem;
    cfg.stream = cudaStreamPerThread;
    cudaLaunchAttribute at[1];
    at[0].id = cudaLaunchAttributeClusterDimension;
    at[0].val.clusterDim.x = cluster.x;
    at[0].val.clusterDim.y = cluster.y;
    at[0].val.clusterDim.z = cluster.z;
    cfg.attrs = at;
    cfg.numAttrs = 1;
    cudaLaunchKernelEx(&cfg, k, KArgs(args)...);
}

extern "C" void kernel_launch(void* const* d_in, const int* in_sizes, int n_in, void* d_out, int out_size) {
    const bf16* x = (const bf16*)d_in[0];
    const bf16* log_A_real = (const bf16*)d_in[1];
    const bf16* A_imag = (const bf16*)d_in[2];
    const bf16* C_real = (const bf16*)d_in[3];
    const bf16* C_imag = (const bf16*)d_in[4];
    const bf16* log_dt = (const bf16*)d_in[5];
    const bf16* D_skip = (const bf16*)d_in[6];
    const bf16* w1 = (const bf16*)d_in[8];
    const bf16* b1 = (const bf16*)d_in[9];
    const bf16* w2 = (const bf16*)d_in[10];
    const bf16* b2 = (const bf16*)d_in[11];
    bf16* out = (bf16*)d_out;

    static bool init = false;
    static CUtensorMap mA1, mB1, mA2, mB2;
    if (!init) {
        void* fn = nullptr;
        void *p_xn, *p_h;
        cudaDriverEntryPointQueryResult qr;
        cudaGetDriverEntryPoint("cuTensorMapEncodeTiled", &fn, cudaEnableDefault, &qr);
        PFN_encodeTiled enc = (PFN_encodeTiled)fn;
        cudaGetSymbolAddress(&p_xn, g_xn);
        cudaGetSymbolAddress(&p_h, g_h);
        make_map(enc, &mA1, p_xn, D_, L_, 64, 128, CU_TENSOR_MAP_SWIZZLE_128B);
        make_map(enc, &mB1, w1, F_, D_, 64, 8, CU_TENSOR_MAP_SWIZZLE_128B);
        make_map(enc, &mA2, p_h, F_, L_, 64, 32, CU_TENSOR_MAP_SWIZZLE_128B);
        make_map(enc, &mB2, w2, D_, F_, 64, 32, CU_TENSOR_MAP_SWIZZLE_128B);
        cudaFuncSetAttribute(k2_conv, cudaFuncAttributeMaxDynamicSharedMemorySize, CV_SMEM);
        cudaFuncSetAttribute(k_g1, cudaFuncAttributeMaxDynamicSharedMemorySize, G1::SMEM);
        cudaFuncSetAttribute(k_g2, cudaFuncAttributeMaxDynamicSharedMemorySize, G2::SMEM);
        init = true;
    }
    k1_prep<<<128, 256>>>(x, log_A_real, A_imag, C_real, C_imag, log_dt);
    k2_conv<<<D_ / CV_CH, 256, CV_SMEM>>>(D_skip);
    launch_cluster(k_g1, dim3(7, 16), dim3(384), G1::SMEM, dim3(1, 8, 1), mA1, mB1, b1);
    launch_cluster(k_g2, dim3(4, 16), dim3(384), G2::SMEM, dim3(4, 2, 1), mA2, mB2, b2, x, out);
}
```

```cpp
#include <cuda_runtime.h>
#include <cuda_bf16.h>
#include <cuda_fp16.h>
#include <cuda.h>
#include <stdint.h>

typedef __nv_bfloat16 bf16;

constexpr int L_ = 2048, D_ = 512, N_ = 128, F_ = 1792;
constexpr int SSM_CTAS = 68;

__device__ __align__(1024) bf16 g_xn[L_ * D_];
__device__ __align__(1024) bf16 g_xT[D_ * L_];
constexpr int KB_PITCH = 648;
__device__ __align__(1024) bf16 g_Kb[D_ * KB_PITCH];
__device__ __align__(1024) bf16 g_sT[D_ * L_];
__device__ __align__(1024) bf16 g_h[L_ * F_];

__device__ unsigned int g_ssm_next;
__device__ unsigned int g_k1_done;
__device__ __align__(16) unsigned int g_hcnt[512];
__device__ unsigned int g_epoch;
__device__ unsigned int g_lncnt[16];

#define QROT 0
#define DBG_T(kid, slot)
#define DBG_P(kid, slot)
#define DBG_W(kid, slot)
#define DBG_END(kid)
__device__ __forceinline__ float bfr(float x) { return __bfloat162float(__float2bfloat16(x)); }
__device__ __forceinline__ uint32_t smem_u32(const void* p) { return (uint32_t)__cvta_generic_to_shared(p); }
__device__ __forceinline__ uint32_t pack_bf16(float lo, float hi) {
    __nv_bfloat162 v = __floats2bfloat162_rn(lo, hi);
    return *reinterpret_cast<uint32_t*>(&v);
}

__device__ __forceinline__ void mbar_init(uint32_t bar, uint32_t count) {
    asm volatile("mbarrier.init.shared::cta.b64 [%0], %1;" ::"r"(bar), "r"(count) : "memory");
}
__device__ __forceinline__ void mbar_expect_tx(uint32_t bar, uint32_t bytes) {
    asm volatile("mbarrier.arrive.expect_tx.shared::cta.b64 _, [%0], %1;" ::"r"(bar), "r"(bytes) : "memory");
}
__device__ __forceinline__ void mbar_arrive(uint32_t bar) {
    asm volatile("mbarrier.arrive.shared::cta.b64 _, [%0];" ::"r"(bar) : "memory");
}
__device__ __forceinline__ void mbar_wait(uint32_t bar, uint32_t parity) {
    uint32_t done;
    int it = 0;
    do {
        asm volatile(
            "{\n.reg .pred p;\n"
            "mbarrier.try_wait.parity.shared::cta.b64 p, [%1], %2;\n"
            "selp.u32 %0, 1, 0, p;\n}\n"
            : "=r"(done) : "r"(bar), "r"(parity) : "memory");
    } while (!done && ++it < (1 << 26));
}
__device__ __forceinline__ void tma_load_2d(uint32_t smem, const CUtensorMap* map, int c0, int c1, uint32_t bar) {
    asm volatile(
        "cp.async.bulk.tensor.2d.shared::cluster.global.mbarrier::complete_tx::bytes [%0], [%1, {%3, %4}], [%2];"
        ::"r"(smem), "l"(reinterpret_cast<uint64_t>(map)), "r"(bar), "r"(c0), "r"(c1) : "memory");
}
__device__ __forceinline__ void tma_load_2d_mc(uint32_t smem, const CUtensorMap* map, int c0, int c1, uint32_t bar,
                                               uint16_t mask) {
    asm volatile(
        "cp.async.bulk.tensor.2d.shared::cluster.global.mbarrier::complete_tx::bytes.multicast::cluster [%0], [%1, {%3, %4}], [%2], %5;"
        ::"r"(smem), "l"(reinterpret_cast<uint64_t>(map)), "r"(bar), "r"(c0), "r"(c1), "h"(mask) : "memory");
}
__device__ __forceinline__ uint32_t mapa(uint32_t addr, uint32_t cta) {
    uint32_t r;
    asm volatile("mapa.shared::cluster.u32 %0, %1, %2;" : "=r"(r) : "r"(addr), "r"(cta));
    return r;
}
__device__ __forceinline__ void mbar_arrive_cluster(uint32_t cluster_addr) {
    asm volatile("mbarrier.arrive.shared::cluster.b64 _, [%0];" ::"r"(cluster_addr) : "memory");
}
__device__ __forceinline__ void cluster_sync_all() {
    asm volatile("barrier.cluster.arrive.release.aligned;\nbarrier.cluster.wait.acquire.aligned;" ::: "memory");
}
__device__ __forceinline__ void wgmma_fence() { asm volatile("wgmma.fence.sync.aligned;" ::: "memory"); }
__device__ __forceinline__ void wgmma_commit() { asm volatile("wgmma.commit_group.sync.aligned;" ::: "memory"); }
template <int N> __device__ __forceinline__ void wgmma_wait() {
    asm volatile("wgmma.wait_group.sync.aligned %0;" ::"n"(N) : "memory");
}
__device__ __forceinline__ uint64_t make_desc(uint32_t addr, uint32_t lbo_bytes, uint32_t sbo_bytes, uint32_t swz = 1) {
    uint64_t d = 0;
    d |= (uint64_t)((addr & 0x3FFFF) >> 4);
    d |= (uint64_t)((lbo_bytes >> 4) & 0x3FFF) << 16;
    d |= (uint64_t)((sbo_bytes >> 4) & 0x3FFF) << 32;
    d |= (uint64_t)swz << 62;
    return d;
}

__device__ __forceinline__ void wgmma_n128(float (&d)[64], uint64_t da, uint64_t db) {
    asm volatile(
        "wgmma.mma_async.sync.aligned.m64n128k16.f32.bf16.bf16 {%0,%1,%2,%3,%4,%5,%6,%7,%8,%9,%10,%11,%12,%13,%14,%15,%16,%17,%18,%19,%20,%21,%22,%23,%24,%25,%26,%27,%28,%29,%30,%31,%32,%33,%34,%35,%36,%37,%38,%39,%40,%41,%42,%43,%44,%45,%46,%47,%48,%49,%50,%51,%52,%53,%54,%55,%56,%57,%58,%59,%60,%61,%62,%63}, %64, %65, 1, 1, 1, 0, 1;\n"
        : "+f"(d[0]), "+f"(d[1]), "+f"(d[2]), "+f"(d[3]), "+f"(d[4]), "+f"(d[5]), "+f"(d[6]), "+f"(d[7]), "+f"(d[8]), "+f"(d[9]), "+f"(d[10]), "+f"(d[11]), "+f"(d[12]), "+f"(d[13]), "+f"(d[14]), "+f"(d[15]), "+f"(d[16]), "+f"(d[17]), "+f"(d[18]), "+f"(d[19]), "+f"(d[20]), "+f"(d[21]), "+f"(d[22]), "+f"(d[23]), "+f"(d[24]), "+f"(d[25]), "+f"(d[26]), "+f"(d[27]), "+f"(d[28]), "+f"(d[29]), "+f"(d[30]), "+f"(d[31]), "+f"(d[32]), "+f"(d[33]), "+f"(d[34]), "+f"(d[35]), "+f"(d[36]), "+f"(d[37]), "+f"(d[38]), "+f"(d[39]), "+f"(d[40]), "+f"(d[41]), "+f"(d[42]), "+f"(d[43]), "+f"(d[44]), "+f"(d[45]), "+f"(d[46]), "+f"(d[47]), "+f"(d[48]), "+f"(d[49]), "+f"(d[50]), "+f"(d[51]), "+f"(d[52]), "+f"(d[53]), "+f"(d[54]), "+f"(d[55]), "+f"(d[56]), "+f"(d[57]), "+f"(d[58]), "+f"(d[59]), "+f"(d[60]), "+f"(d[61]), "+f"(d[62]), "+f"(d[63])
        : "l"(da), "l"(db));
}

__device__ __forceinline__ void wgmma_n256(float (&d)[128], uint64_t da, uint64_t db) {
    asm volatile(
        "wgmma.mma_async.sync.aligned.m64n256k16.f32.bf16.bf16 {%0,%1,%2,%3,%4,%5,%6,%7,%8,%9,%10,%11,%12,%13,%14,%15,%16,%17,%18,%19,%20,%21,%22,%23,%24,%25,%26,%27,%28,%29,%30,%31,%32,%33,%34,%35,%36,%37,%38,%39,%40,%41,%42,%43,%44,%45,%46,%47,%48,%49,%50,%51,%52,%53,%54,%55,%56,%57,%58,%59,%60,%61,%62,%63,%64,%65,%66,%67,%68,%69,%70,%71,%72,%73,%74,%75,%76,%77,%78,%79,%80,%81,%82,%83,%84,%85,%86,%87,%88,%89,%90,%91,%92,%93,%94,%95,%96,%97,%98,%99,%100,%101,%102,%103,%104,%105,%106,%107,%108,%109,%110,%111,%112,%113,%114,%115,%116,%117,%118,%119,%120,%121,%122,%123,%124,%125,%126,%127}, %128, %129, 1, 1, 1, 0, 1;\n"
        : "+f"(d[0]), "+f"(d[1]), "+f"(d[2]), "+f"(d[3]), "+f"(d[4]), "+f"(d[5]), "+f"(d[6]), "+f"(d[7]), "+f"(d[8]), "+f"(d[9]), "+f"(d[10]), "+f"(d[11]), "+f"(d[12]), "+f"(d[13]), "+f"(d[14]), "+f"(d[15]), "+f"(d[16]), "+f"(d[17]), "+f"(d[18]), "+f"(d[19]), "+f"(d[20]), "+f"(d[21]), "+f"(d[22]), "+f"(d[23]), "+f"(d[24]), "+f"(d[25]), "+f"(d[26]), "+f"(d[27]), "+f"(d[28]), "+f"(d[29]), "+f"(d[30]), "+f"(d[31]), "+f"(d[32]), "+f"(d[33]), "+f"(d[34]), "+f"(d[35]), "+f"(d[36]), "+f"(d[37]), "+f"(d[38]), "+f"(d[39]), "+f"(d[40]), "+f"(d[41]), "+f"(d[42]), "+f"(d[43]), "+f"(d[44]), "+f"(d[45]), "+f"(d[46]), "+f"(d[47]), "+f"(d[48]), "+f"(d[49]), "+f"(d[50]), "+f"(d[51]), "+f"(d[52]), "+f"(d[53]), "+f"(d[54]), "+f"(d[55]), "+f"(d[56]), "+f"(d[57]), "+f"(d[58]), "+f"(d[59]), "+f"(d[60]), "+f"(d[61]), "+f"(d[62]), "+f"(d[63]), "+f"(d[64]), "+f"(d[65]), "+f"(d[66]), "+f"(d[67]), "+f"(d[68]), "+f"(d[69]), "+f"(d[70]), "+f"(d[71]), "+f"(d[72]), "+f"(d[73]), "+f"(d[74]), "+f"(d[75]), "+f"(d[76]), "+f"(d[77]), "+f"(d[78]), "+f"(d[79]), "+f"(d[80]), "+f"(d[81]), "+f"(d[82]), "+f"(d[83]), "+f"(d[84]), "+f"(d[85]), "+f"(d[86]), "+f"(d[87]), "+f"(d[88]), "+f"(d[89]), "+f"(d[90]), "+f"(d[91]), "+f"(d[92]), "+f"(d[93]), "+f"(d[94]), "+f"(d[95]), "+f"(d[96]), "+f"(d[97]), "+f"(d[98]), "+f"(d[99]), "+f"(d[100]), "+f"(d[101]), "+f"(d[102]), "+f"(d[103]), "+f"(d[104]), "+f"(d[105]), "+f"(d[106]), "+f"(d[107]), "+f"(d[108]), "+f"(d[109]), "+f"(d[110]), "+f"(d[111]), "+f"(d[112]), "+f"(d[113]), "+f"(d[114]), "+f"(d[115]), "+f"(d[116]), "+f"(d[117]), "+f"(d[118]), "+f"(d[119]), "+f"(d[120]), "+f"(d[121]), "+f"(d[122]), "+f"(d[123]), "+f"(d[124]), "+f"(d[125]), "+f"(d[126]), "+f"(d[127])
        : "l"(da), "l"(db));
}

__device__ __forceinline__ void wgmma_n256_rs(float (&d)[128], uint32_t a0, uint32_t a1, uint32_t a2, uint32_t a3, uint64_t db) {
    asm volatile(
        "wgmma.mma_async.sync.aligned.m64n256k16.f32.bf16.bf16 {%0,%1,%2,%3,%4,%5,%6,%7,%8,%9,%10,%11,%12,%13,%14,%15,%16,%17,%18,%19,%20,%21,%22,%23,%24,%25,%26,%27,%28,%29,%30,%31,%32,%33,%34,%35,%36,%37,%38,%39,%40,%41,%42,%43,%44,%45,%46,%47,%48,%49,%50,%51,%52,%53,%54,%55,%56,%57,%58,%59,%60,%61,%62,%63,%64,%65,%66,%67,%68,%69,%70,%71,%72,%73,%74,%75,%76,%77,%78,%79,%80,%81,%82,%83,%84,%85,%86,%87,%88,%89,%90,%91,%92,%93,%94,%95,%96,%97,%98,%99,%100,%101,%102,%103,%104,%105,%106,%107,%108,%109,%110,%111,%112,%113,%114,%115,%116,%117,%118,%119,%120,%121,%122,%123,%124,%125,%126,%127}, {%128,%129,%130,%131}, %132, 1, 1, 1, 1;\n"
        : "+f"(d[0]), "+f"(d[1]), "+f"(d[2]), "+f"(d[3]), "+f"(d[4]), "+f"(d[5]), "+f"(d[6]), "+f"(d[7]), "+f"(d[8]), "+f"(d[9]), "+f"(d[10]), "+f"(d[11]), "+f"(d[12]), "+f"(d[13]), "+f"(d[14]), "+f"(d[15]), "+f"(d[16]), "+f"(d[17]), "+f"(d[18]), "+f"(d[19]), "+f"(d[20]), "+f"(d[21]), "+f"(d[22]), "+f"(d[23]), "+f"(d[24]), "+f"(d[25]), "+f"(d[26]), "+f"(d[27]), "+f"(d[28]), "+f"(d[29]), "+f"(d[30]), "+f"(d[31]), "+f"(d[32]), "+f"(d[33]), "+f"(d[34]), "+f"(d[35]), "+f"(d[36]), "+f"(d[37]), "+f"(d[38]), "+f"(d[39]), "+f"(d[40]), "+f"(d[41]), "+f"(d[42]), "+f"(d[43]), "+f"(d[44]), "+f"(d[45]), "+f"(d[46]), "+f"(d[47]), "+f"(d[48]), "+f"(d[49]), "+f"(d[50]), "+f"(d[51]), "+f"(d[52]), "+f"(d[53]), "+f"(d[54]), "+f"(d[55]), "+f"(d[56]), "+f"(d[57]), "+f"(d[58]), "+f"(d[59]), "+f"(d[60]), "+f"(d[61]), "+f"(d[62]), "+f"(d[63]), "+f"(d[64]), "+f"(d[65]), "+f"(d[66]), "+f"(d[67]), "+f"(d[68]), "+f"(d[69]), "+f"(d[70]), "+f"(d[71]), "+f"(d[72]), "+f"(d[73]), "+f"(d[74]), "+f"(d[75]), "+f"(d[76]), "+f"(d[77]), "+f"(d[78]), "+f"(d[79]), "+f"(d[80]), "+f"(d[81]), "+f"(d[82]), "+f"(d[83]), "+f"(d[84]), "+f"(d[85]), "+f"(d[86]), "+f"(d[87]), "+f"(d[88]), "+f"(d[89]), "+f"(d[90]), "+f"(d[91]), "+f"(d[92]), "+f"(d[93]), "+f"(d[94]), "+f"(d[95]), "+f"(d[96]), "+f"(d[97]), "+f"(d[98]), "+f"(d[99]), "+f"(d[100]), "+f"(d[101]), "+f"(d[102]), "+f"(d[103]), "+f"(d[104]), "+f"(d[105]), "+f"(d[106]), "+f"(d[107]), "+f"(d[108]), "+f"(d[109]), "+f"(d[110]), "+f"(d[111]), "+f"(d[112]), "+f"(d[113]), "+f"(d[114]), "+f"(d[115]), "+f"(d[116]), "+f"(d[117]), "+f"(d[118]), "+f"(d[119]), "+f"(d[120]), "+f"(d[121]), "+f"(d[122]), "+f"(d[123]), "+f"(d[124]), "+f"(d[125]), "+f"(d[126]), "+f"(d[127])
        : "r"(a0), "r"(a1), "r"(a2), "r"(a3), "l"(db));
}

__device__ __forceinline__ void wgmma_rs(float (&d)[64], uint32_t a0, uint32_t a1, uint32_t a2, uint32_t a3, uint64_t db) {
    asm volatile("wgmma.mma_async.sync.aligned.m64n128k16.f32.bf16.bf16 {%0,%1,%2,%3,%4,%5,%6,%7,%8,%9,%10,%11,%12,%13,%14,%15,%16,%17,%18,%19,%20,%21,%22,%23,%24,%25,%26,%27,%28,%29,%30,%31,%32,%33,%34,%35,%36,%37,%38,%39,%40,%41,%42,%43,%44,%45,%46,%47,%48,%49,%50,%51,%52,%53,%54,%55,%56,%57,%58,%59,%60,%61,%62,%63}, {%64,%65,%66,%67}, %68, 1, 1, 1, 0;\n"
        : "+f"(d[0]), "+f"(d[1]), "+f"(d[2]), "+f"(d[3]), "+f"(d[4]), "+f"(d[5]), "+f"(d[6]), "+f"(d[7]), "+f"(d[8]), "+f"(d[9]), "+f"(d[10]), "+f"(d[11]), "+f"(d[12]), "+f"(d[13]), "+f"(d[14]), "+f"(d[15]), "+f"(d[16]), "+f"(d[17]), "+f"(d[18]), "+f"(d[19]), "+f"(d[20]), "+f"(d[21]), "+f"(d[22]), "+f"(d[23]), "+f"(d[24]), "+f"(d[25]), "+f"(d[26]), "+f"(d[27]), "+f"(d[28]), "+f"(d[29]), "+f"(d[30]), "+f"(d[31]), "+f"(d[32]), "+f"(d[33]), "+f"(d[34]), "+f"(d[35]), "+f"(d[36]), "+f"(d[37]), "+f"(d[38]), "+f"(d[39]), "+f"(d[40]), "+f"(d[41]), "+f"(d[42]), "+f"(d[43]), "+f"(d[44]), "+f"(d[45]), "+f"(d[46]), "+f"(d[47]), "+f"(d[48]), "+f"(d[49]), "+f"(d[50]), "+f"(d[51]), "+f"(d[52]), "+f"(d[53]), "+f"(d[54]), "+f"(d[55]), "+f"(d[56]), "+f"(d[57]), "+f"(d[58]), "+f"(d[59]), "+f"(d[60]), "+f"(d[61]), "+f"(d[62]), "+f"(d[63]) : "r"(a0), "r"(a1), "r"(a2), "r"(a3), "l"(db));
}
__device__ __forceinline__ void wgmma_rs(float (&d)[48], uint32_t a0, uint32_t a1, uint32_t a2, uint32_t a3, uint64_t db) {
    asm volatile("wgmma.mma_async.sync.aligned.m64n96k16.f32.bf16.bf16 {%0,%1,%2,%3,%4,%5,%6,%7,%8,%9,%10,%11,%12,%13,%14,%15,%16,%17,%18,%19,%20,%21,%22,%23,%24,%25,%26,%27,%28,%29,%30,%31,%32,%33,%34,%35,%36,%37,%38,%39,%40,%41,%42,%43,%44,%45,%46,%47}, {%48,%49,%50,%51}, %52, 1, 1, 1, 0;\n"
        : "+f"(d[0]), "+f"(d[1]), "+f"(d[2]), "+f"(d[3]), "+f"(d[4]), "+f"(d[5]), "+f"(d[6]), "+f"(d[7]), "+f"(d[8]), "+f"(d[9]), "+f"(d[10]), "+f"(d[11]), "+f"(d[12]), "+f"(d[13]), "+f"(d[14]), "+f"(d[15]), "+f"(d[16]), "+f"(d[17]), "+f"(d[18]), "+f"(d[19]), "+f"(d[20]), "+f"(d[21]), "+f"(d[22]), "+f"(d[23]), "+f"(d[24]), "+f"(d[25]), "+f"(d[26]), "+f"(d[27]), "+f"(d[28]), "+f"(d[29]), "+f"(d[30]), "+f"(d[31]), "+f"(d[32]), "+f"(d[33]), "+f"(d[34]), "+f"(d[35]), "+f"(d[36]), "+f"(d[37]), "+f"(d[38]), "+f"(d[39]), "+f"(d[40]), "+f"(d[41]), "+f"(d[42]), "+f"(d[43]), "+f"(d[44]), "+f"(d[45]), "+f"(d[46]), "+f"(d[47]) : "r"(a0), "r"(a1), "r"(a2), "r"(a3), "l"(db));
}
__device__ __forceinline__ void wgmma_rs(float (&d)[32], uint32_t a0, uint32_t a1, uint32_t a2, uint32_t a3, uint64_t db) {
    asm volatile("wgmma.mma_async.sync.aligned.m64n64k16.f32.bf16.bf16 {%0,%1,%2,%3,%4,%5,%6,%7,%8,%9,%10,%11,%12,%13,%14,%15,%16,%17,%18,%19,%20,%21,%22,%23,%24,%25,%26,%27,%28,%29,%30,%31}, {%32,%33,%34,%35}, %36, 1, 1, 1, 0;\n"
        : "+f"(d[0]), "+f"(d[1]), "+f"(d[2]), "+f"(d[3]), "+f"(d[4]), "+f"(d[5]), "+f"(d[6]), "+f"(d[7]), "+f"(d[8]), "+f"(d[9]), "+f"(d[10]), "+f"(d[11]), "+f"(d[12]), "+f"(d[13]), "+f"(d[14]), "+f"(d[15]), "+f"(d[16]), "+f"(d[17]), "+f"(d[18]), "+f"(d[19]), "+f"(d[20]), "+f"(d[21]), "+f"(d[22]), "+f"(d[23]), "+f"(d[24]), "+f"(d[25]), "+f"(d[26]), "+f"(d[27]), "+f"(d[28]), "+f"(d[29]), "+f"(d[30]), "+f"(d[31]) : "r"(a0), "r"(a1), "r"(a2), "r"(a3), "l"(db));
}
__device__ __forceinline__ void wgmma_rs(float (&d)[16], uint32_t a0, uint32_t a1, uint32_t a2, uint32_t a3, uint64_t db) {
    asm volatile("wgmma.mma_async.sync.aligned.m64n32k16.f32.bf16.bf16 {%0,%1,%2,%3,%4,%5,%6,%7,%8,%9,%10,%11,%12,%13,%14,%15}, {%16,%17,%18,%19}, %20, 1, 1, 1, 0;\n"
        : "+f"(d[0]), "+f"(d[1]), "+f"(d[2]), "+f"(d[3]), "+f"(d[4]), "+f"(d[5]), "+f"(d[6]), "+f"(d[7]), "+f"(d[8]), "+f"(d[9]), "+f"(d[10]), "+f"(d[11]), "+f"(d[12]), "+f"(d[13]), "+f"(d[14]), "+f"(d[15]) : "r"(a0), "r"(a1), "r"(a2), "r"(a3), "l"(db));
}

__device__ __forceinline__ void mma_bf16(float (&c)[4], uint32_t a0, uint32_t a1, uint32_t a2, uint32_t a3,
                                         uint32_t b0, uint32_t b1) {
    asm volatile(
        "mma.sync.aligned.m16n8k16.row.col.f32.bf16.bf16.f32 {%0,%1,%2,%3}, {%4,%5,%6,%7}, {%8,%9}, {%0,%1,%2,%3};"
        : "+f"(c[0]), "+f"(c[1]), "+f"(c[2]), "+f"(c[3])
        : "r"(a0), "r"(a1), "r"(a2), "r"(a3), "r"(b0), "r"(b1));
}
__device__ __forceinline__ void mma_tf32(float (&c)[4], uint32_t a0, uint32_t a1, uint32_t a2, uint32_t a3,
                                         uint32_t b0, uint32_t b1) {
    asm volatile(
        "mma.sync.aligned.m16n8k8.row.col.f32.tf32.tf32.f32 {%0,%1,%2,%3}, {%4,%5,%6,%7}, {%8,%9}, {%0,%1,%2,%3};"
        : "+f"(c[0]), "+f"(c[1]), "+f"(c[2]), "+f"(c[3])
        : "r"(a0), "r"(a1), "r"(a2), "r"(a3), "r"(b0), "r"(b1));
}
__device__ __forceinline__ uint32_t to_tf32(float x) {
    return __float_as_uint(x) + 0x1000u;
}
__device__ __forceinline__ void ldmatrix_x4(uint32_t& r0, uint32_t& r1, uint32_t& r2, uint32_t& r3, uint32_t addr) {
    asm volatile("ldmatrix.sync.aligned.m8n8.x4.shared.b16 {%0,%1,%2,%3}, [%4];"
                 : "=r"(r0), "=r"(r1), "=r"(r2), "=r"(r3) : "r"(addr));
}

__device__ __forceinline__ void stmatrix_x4(uint32_t addr, uint32_t r0, uint32_t r1, uint32_t r2, uint32_t r3) {
    asm volatile("stmatrix.sync.aligned.m8n8.x4.shared.b16 [%0], {%1,%2,%3,%4};" ::"r"(addr), "r"(r0), "r"(r1), "r"(r2), "r"(r3) : "memory");
}
__device__ __forceinline__ void tma_store_2d(const CUtensorMap* map, uint32_t smem, int c0, int c1) {
    asm volatile("cp.async.bulk.tensor.2d.global.shared::cta.bulk_group [%0, {%2, %3}], [%1];"
                 ::"l"(reinterpret_cast<uint64_t>(map)), "r"(smem), "r"(c0), "r"(c1) : "memory");
}
__device__ __forceinline__ void named_bar(int id, int n) { asm volatile("bar.sync %0, %1;" ::"r"(id), "r"(n) : "memory"); }
__device__ __forceinline__ void fence_async() { asm volatile("fence.proxy.async.shared::cta;" ::: "memory"); }

__device__ __forceinline__ uint32_t hadd2(uint32_t a, uint32_t b) { uint32_t r; asm("add.rn.bf16x2 %0, %1, %2;" : "=r"(r) : "r"(a), "r"(b)); return r; }
__device__ __forceinline__ uint32_t hmul2(uint32_t a, uint32_t b) { uint32_t r; asm("mul.rn.bf16x2 %0, %1, %2;" : "=r"(r) : "r"(a), "r"(b)); return r; }
__device__ __forceinline__ uint32_t hmax2(uint32_t a, uint32_t b) { uint32_t r; asm("max.bf16x2 %0, %1, %2;" : "=r"(r) : "r"(a), "r"(b)); return r; }
__device__ __forceinline__ uint32_t hfma2(uint32_t a, uint32_t b, uint32_t c) { uint32_t r; asm("fma.rn.bf16x2 %0, %1, %2, %3;" : "=r"(r) : "r"(a), "r"(b), "r"(c)); return r; }
__device__ __forceinline__ float silu_h(float hv) {
    float th;
    asm("tanh.approx.f32 %0, %1;" : "=f"(th) : "f"(hv));
    return fmaf(hv, th, hv);
}
__device__ __forceinline__ float silu_f(float v) {
    float th;
    const float hv = 0.5f * v;
    asm("tanh.approx.f32 %0, %1;" : "=f"(th) : "f"(hv));
    return fmaf(hv, th, hv);
    float e, r;
    asm("ex2.approx.ftz.f32 %0, %1;" : "=f"(e) : "f"(-1.4426950408889634f * v));
    asm("rcp.approx.ftz.f32 %0, %1;" : "=f"(r) : "f"(1.f + e));
    return v * r;
}

__device__ __forceinline__ void pdl_wait() { asm volatile("griddepcontrol.wait;" ::: "memory"); }
__device__ __forceinline__ void pdl_launch() { asm volatile("griddepcontrol.launch_dependents;" ::: "memory"); }

#define ORD 1
#define LNF 1
__device__ __forceinline__ void signal(unsigned int* cnt) {
    asm volatile("fence.acq_rel.gpu;\nred.relaxed.gpu.global.add.u32 [%0], 1;" ::"l"(cnt) : "memory");
}
__device__ __forceinline__ void wait_count(const unsigned int* cnt, unsigned int per_launch) {
    unsigned int e, v;
    asm volatile("ld.relaxed.gpu.global.u32 %0, [%2];\nld.acquire.gpu.global.u32 %1, [%3];" : "=r"(e), "=r"(v) : "l"(&g_epoch), "l"(cnt) : "memory");
    for (int it = 0; (int)(v - e * per_launch) < 0 && it < (1 << 22); ++it) {
        __nanosleep(20);
        asm volatile("ld.acquire.gpu.global.u32 %0, [%1];" : "=r"(v) : "l"(cnt) : "memory");
    }
    DBG_P(0, 60);
    asm volatile("fence.proxy.async.global;" ::: "memory");
    DBG_P(0, 61);
}

struct cplx { float r, i; };
__device__ __forceinline__ cplx cmul(cplx a, cplx b) { return {a.r * b.r - a.i * b.i, a.r * b.i + a.i * b.r}; }
__device__ __forceinline__ cplx csq(cplx a) { return {a.r * a.r - a.i * a.i, 2.f * a.r * a.i}; }
__device__ __forceinline__ cplx cexp_(float ar, float ai) {
    float m = expf(ar), s, c;
    sincosf(ai, &s, &c);
    return {m * c, m * s};
}

struct SsmParams { const bf16 *log_A_real, *A_imag, *C_real, *C_imag, *log_dt, *D_skip; };
__device__ __forceinline__ cplx cmulc(cplx a, cplx b) { return {a.r * b.r + a.i * b.i, a.i * b.r - a.r * b.i}; }

struct KMode { uint32_t lar, aim, cr, ci; };
__device__ __forceinline__ uint32_t ld_bf(const bf16* p) {
    uint32_t r;
    asm volatile("ld.global.nc.u16 %0, [%1];" : "=r"(r) : "l"(p));
    return r;
}
__device__ __forceinline__ float bits_f(uint32_t b) { return __uint_as_float(b << 16); }
__device__ __forceinline__ KMode kgen_load(const SsmParams& P, int m) {
    return {ld_bf(P.log_A_real + m), ld_bf(P.A_imag + m), ld_bf(P.C_real + m), ld_bf(P.C_imag + m)};
}
constexpr int KG_TAB = 2816;
__device__ __forceinline__ cplx zpow(float a2, float b, float e) {
    float mag, sn, cs;
    asm("ex2.approx.ftz.f32 %0, %1;" : "=f"(mag) : "f"(a2 * e));
    asm("sin.approx.ftz.f32 %0, %1;" : "=f"(sn) : "f"(b * e));
    asm("cos.approx.ftz.f32 %0, %1;" : "=f"(cs) : "f"(b * e));
    return {mag * cs, mag * sn};
}
__device__ __forceinline__ void kgen_group(const KMode& km, float dt, unsigned char* tab, float (&acc)[5][4], float& k2048) {
    const int lane = threadIdx.x & 31, g = lane >> 2, t = lane & 3;
    float4* t1 = reinterpret_cast<float4*>(tab);
    float2* t2 = reinterpret_cast<float2*>(tab + 1024);
    {
        const float a2 = -bfr(expf(bits_f(km.lar))) * dt * 1.4426950408889634f;
        const float nb = -bits_f(km.aim) * dt;
        const cplx Cm = {bits_f(km.cr) * dt, bits_f(km.ci) * dt};
        const cplx c8 = zpow(a2, nb, 8.f), c64 = zpow(a2, nb, 64.f), c240 = zpow(a2, nb, 240.f);
        const cplx c128 = csq(c64), c256 = csq(c128), c512 = csq(c256), c1024 = csq(c512), c2048 = csq(c1024);
        const cplx c752 = cmul(c512, c240), c1264 = cmul(c1024, c240), c1504 = cmul(c1264, c240), c1744 = cmul(c1504, c240);
        k2048 += Cm.r * c2048.r + Cm.i * c2048.i;
        __syncwarp();
        t1[2 * lane] = make_float4(a2, nb, Cm.r, Cm.i);
        t1[2 * lane + 1] = make_float4(c128.r, c128.i, c8.r, c8.i);
        float2* cp = t2 + lane * 7;
        cp[0] = make_float2(c256.r, c256.i);
        cp[1] = make_float2(c512.r, c512.i);
        cp[2] = make_float2(c752.r, c752.i);
        cp[3] = make_float2(c1024.r, c1024.i);
        cp[4] = make_float2(c1264.r, c1264.i);
        cp[5] = make_float2(c1504.r, c1504.i);
        cp[6] = make_float2(c1744.r, c1744.i);
        __syncwarp();
    }
    const float fg = (float)g;
    const float4* r1 = t1 + 2 * t;
    const float2 *r2 = t2 + 7 * t, *r3 = r2 + 1 + (g >> 2), *r4 = r2 + 3 + (g >> 1);
#define KUNR 2
    constexpr int kunr = KUNR;
#pragma unroll kunr
    for (int ks = 0; ks < 8; ++ks) {
        const float4 k0 = r1[8 * ks], k1 = r1[8 * ks + 1];
        const float2 k2 = r2[28 * ks], k3 = r3[28 * ks], k4 = r4[28 * ks];
        const cplx p1 = zpow(k0.x, k0.y, fg);
        const cplx p2 = csq(p1), p4 = csq(p2), p8 = csq(p4), p16 = csq(p8);
        const cplx lo = cmulc({k0.z, k0.w}, p16), hi = cmulc(lo, {k1.x, k1.y});
        const cplx b1 = cmul(p1, {k1.z, k1.w}), b2 = cmul(p2, {k2.x, k2.y}), b3 = cmul(p4, {k3.x, k3.y}), b4 = cmul(p8, {k4.x, k4.y});
#define U32(x) __float_as_uint(x)
        mma_tf32(acc[0], U32(lo.r), U32(hi.r), U32(lo.i), U32(hi.i), U32(p1.r), U32(p1.i));
        mma_tf32(acc[1], U32(lo.r), U32(hi.r), U32(lo.i), U32(hi.i), U32(b1.r), U32(b1.i));
        mma_tf32(acc[2], U32(lo.r), U32(hi.r), U32(lo.i), U32(hi.i), U32(b2.r), U32(b2.i));
        mma_tf32(acc[3], U32(lo.r), U32(hi.r), U32(lo.i), U32(hi.i), U32(b3.r), U32(b3.i));
        mma_tf32(acc[4], U32(lo.r), U32(hi.r), U32(lo.i), U32(hi.i), U32(b4.r), U32(b4.i));
#undef U32
    }
}
constexpr float KSC = 2.0014f * 0.03125f, KSC_END = 2.f * 0.03125f;
__device__ __forceinline__ void kgen_part(float* Kp, const float (&acc)[5][4], float k2048) {
    const int lane = threadIdx.x & 31, g = lane >> 2, t = lane & 3;
#pragma unroll
    for (int o = 16; o; o >>= 1) k2048 += __shfl_xor_sync(0xffffffffu, k2048, o);
    if (lane == 0) *reinterpret_cast<float2*>(Kp + 640) = make_float2(k2048, 0.f);
#pragma unroll
    for (int hh = 0; hh < 2; ++hh) {
        const int i = g + 8 * hh;
        *reinterpret_cast<float2*>(Kp + 16 * i + 2 * t) = make_float2(acc[0][2 * hh], acc[0][2 * hh + 1]);
        *reinterpret_cast<float2*>(Kp + 16 * i + 8 + 2 * t) = make_float2(acc[1][2 * hh], acc[1][2 * hh + 1]);
        *reinterpret_cast<float2*>(Kp + 256 + 8 * i + 2 * t) = make_float2(acc[2][2 * hh], acc[2][2 * hh + 1]);
        *reinterpret_cast<float2*>(Kp + 384 + 4 * i + 2 * (t & 1) + 64 * (t >> 1)) = make_float2(acc[3][2 * hh], acc[3][2 * hh + 1]);
        *reinterpret_cast<float2*>(Kp + 512 + 2 * i + 32 * t) = make_float2(acc[4][2 * hh], acc[4][2 * hh + 1]);
    }
}
#define PF 3
__device__ __forceinline__ void kgen_role(const SsmParams& P, unsigned char* sm, int c, const bf16* w1, const bf16* w2) {
    const int tl = threadIdx.x & 127, wq = tl >> 5;
    const uint32_t ldt = ld_bf(P.log_dt + c);
    const KMode km = kgen_load(P, c * N_ + tl);
#define PFL 0
    const float dt = bfr(expf(bits_f(ldt)));
    if (PF >= 1 && tl == 0 && (!PFL || (km.lar | km.aim | km.cr | km.ci | ldt) < 0x10000u))
        asm volatile("cp.async.bulk.prefetch.L2.global [%0], %1;" ::"l"(w1 + (size_t)c * F_), "r"(F_ * 2) : "memory");
    __syncwarp();
    float acc[5][4], k2048 = 0.f;
#pragma unroll
    for (int s = 0; s < 5; ++s)
#pragma unroll
        for (int i = 0; i < 4; ++i) acc[s][i] = 0.f;
    kgen_group(km, dt, sm + wq * KG_TAB, acc, k2048);
    if (PF == 3 && tl == 32)
        asm volatile("cp.async.bulk.prefetch.L2.global [%0], %1;" ::"l"(w2 + (size_t)c * F_), "r"(F_ * 2) : "memory");
    __syncwarp();
    kgen_part(reinterpret_cast<float*>(sm + wq * KG_TAB), acc, k2048);
    named_bar(1 + (threadIdx.x >> 7), 128);
    const float2* part = reinterpret_cast<const float2*>(sm);
    uint32_t* dst = reinterpret_cast<uint32_t*>(g_Kb + (size_t)c * KB_PITCH);
    for (int i = tl; i < 321; i += 128) {
        const float2 a0 = part[i], a1 = part[KG_TAB / 8 + i], a2 = part[2 * (KG_TAB / 8) + i], a3 = part[3 * (KG_TAB / 8) + i];
        const float sc = i < 320 ? KSC : KSC_END;
        dst[i] = pack_bf16(sc * (a0.x + a1.x + a2.x + a3.x), sc * (a0.y + a1.y + a2.y + a3.y));
    }
}

constexpr int LN_BLOCKS = 128;
#define K1W 2
constexpr int K1_BLOCKS = LN_BLOCKS + D_ / K1W, LN_RPW = 4 / K1W;
constexpr int GEN_SMEM = 4 * KG_TAB;
__global__ void __launch_bounds__(128 * K1W) k1_prep(const bf16* __restrict__ x, const __grid_constant__ SsmParams P,
                                               const bf16* __restrict__ w1, const bf16* __restrict__ w2) {
    __shared__ __align__(16) unsigned char smraw[K1W * GEN_SMEM];
    const int warp = threadIdx.x >> 5, lane = threadIdx.x & 31;
#define LNLAST 0
    const int bid = LNLAST ? (blockIdx.x + LN_BLOCKS) % K1_BLOCKS : blockIdx.x;
    DBG_T(2, 0);
    if (bid == LN_BLOCKS) {
        for (int i = threadIdx.x; i < 512; i += 128 * K1W) g_hcnt[i] = 0;
        if (threadIdx.x == 0) { g_epoch = g_epoch + 1; g_k1_done = 0; g_ssm_next = 144; }
        __threadfence();
        __syncthreads();
    }
    pdl_launch();
    if (bid >= LN_BLOCKS) {
        kgen_role(P, smraw + (threadIdx.x >> 7) * GEN_SMEM, (bid - LN_BLOCKS) * K1W + (threadIdx.x >> 7), w1, w2);
        DBG_T(2, 2);
        DBG_END(2);
        return;
    }
    bf16* tile = reinterpret_cast<bf16*>(smraw);
    const int l0 = bid * 16;
    uint4 v0[LN_RPW], v1[LN_RPW];
#pragma unroll
    for (int rr = 0; rr < LN_RPW; ++rr) {
        const bf16* row = x + (size_t)(l0 + warp * LN_RPW + rr) * D_;
        v0[rr] = __ldg(reinterpret_cast<const uint4*>(row + lane * 8));
        v1[rr] = __ldg(reinterpret_cast<const uint4*>(row + 256 + lane * 8));
    }
#define SENL 0
    auto marker = [&]() {
        uint4* sp = reinterpret_cast<uint4*>(g_sT) + bid * 1024 + threadIdx.x;
#pragma unroll
        for (int i = 0; i < 8 / K1W; ++i) sp[i * 128 * K1W] = make_uint4(~0u, ~0u, ~0u, ~0u);
    };
    if (!SENL) marker();
#pragma unroll
    for (int rr = 0; rr < LN_RPW; ++rr) {
        const int r = warp * LN_RPW + rr;
        float f[16];
        const bf16* p0 = reinterpret_cast<const bf16*>(&v0[rr]);
        const bf16* p1 = reinterpret_cast<const bf16*>(&v1[rr]);
#pragma unroll
        for (int i = 0; i < 8; ++i) { f[i] = __bfloat162float(p0[i]); f[8 + i] = __bfloat162float(p1[i]); }
        float sum = 0.f;
#pragma unroll
        for (int i = 0; i < 16; ++i) sum += f[i];
#pragma unroll
        for (int o = 16; o; o >>= 1) sum += __shfl_xor_sync(0xffffffffu, sum, o);
        const float mean = sum * (1.f / D_);
        float vs = 0.f;
#pragma unroll
        for (int i = 0; i < 16; ++i) { float d = f[i] - mean; vs += d * d; }
#pragma unroll
        for (int o = 16; o; o >>= 1) vs += __shfl_xor_sync(0xffffffffu, vs, o);
        const float m_b = bfr(mean);
        const float v_b = bfr(vs * (1.f / D_));
        const float den = bfr(sqrtf(bfr(v_b + 1e-5f)));
        uint4 o0, o1;
        bf16* q0 = reinterpret_cast<bf16*>(&o0);
        bf16* q1 = reinterpret_cast<bf16*>(&o1);
#pragma unroll
        for (int i = 0; i < 8; ++i) {
            q0[i] = __float2bfloat16(__fdividef(bfr(f[i] - m_b), den));
            q1[i] = __float2bfloat16(__fdividef(bfr(f[8 + i] - m_b), den));
        }
        *reinterpret_cast<uint4*>(g_xn + (size_t)(l0 + r) * D_ + lane * 8) = o0;
        *reinterpret_cast<uint4*>(g_xn + (size_t)(l0 + r) * D_ + 256 + lane * 8) = o1;
        *reinterpret_cast<uint4*>(tile + r * 520 + lane * 8) = o0;
        *reinterpret_cast<uint4*>(tile + r * 520 + 256 + lane * 8) = o1;
    }
    __syncthreads();
    if (threadIdx.x == 0) signal(g_lncnt + (bid >> 3));
    DBG_T(2, 1);
    {
        const int mi = lane >> 3, j = lane & 7;
        const int row = 4 * (j >> 1) + 2 * (mi & 1) + (j & 1);
        const uint32_t a0 = smem_u32(tile + row * 520 + (mi >> 1) * 8);
        bf16* dst = g_xT + (size_t)(lane >> 2) * L_ + l0 + (lane & 3) * 4;
#pragma unroll
        for (int it = 0; it < 8 / K1W; ++it) {
            const int c = (warp * (8 / K1W) + it) * 16;
            uint32_t r0, r1, r2, r3;
            asm volatile("ldmatrix.sync.aligned.m8n8.x4.trans.shared.b16 {%0,%1,%2,%3}, [%4];"
                         : "=r"(r0), "=r"(r1), "=r"(r2), "=r"(r3) : "r"(a0 + c * 2));
            *reinterpret_cast<uint2*>(dst + (size_t)c * L_) = make_uint2(r0, r1);
            *reinterpret_cast<uint2*>(dst + (size_t)(c + 8) * L_) = make_uint2(r2, r3);
        }
    }
    if (SENL) marker();
    DBG_T(2, 2);
    DBG_END(2);
}

constexpr int SS_U = 5120;
constexpr int SS_KB = KB_PITCH * 2;
constexpr int SS_PK = 2112 * 4;
constexpr int SS_R = 4 * 4096;
constexpr int SS_KBOFF = 196608 + 3 * SS_U;
__device__ __forceinline__ int ss_u(int slot) { return ((slot & 1) ? 163840 : 196608) + (slot >> 1) * SS_U; }
__device__ __forceinline__ int ss_pk(int wg) { return 114688 + wg * SS_PK; }
__device__ __forceinline__ int ss_r(int wg) { return wg < 2 ? 16384 + wg * SS_R : 65536; }
constexpr int STG = 49152;
constexpr int MAIN_SMEM = 4 * STG + 24576 + 1024;
constexpr int SSM_STATIC = 144;

__device__ __forceinline__ void bulk_load(uint32_t dst, const void* src, uint32_t bytes, uint32_t bar) {
    asm volatile("cp.async.bulk.shared::cluster.global.mbarrier::complete_tx::bytes [%0], [%1], %2, [%3];"
                 ::"r"(dst), "l"(src), "r"(bytes), "r"(bar) : "memory");
}
template <int NR>
__device__ __forceinline__ void conv_phase(float (&acc)[NR], uint32_t pkp, uint32_t ubase) {
    constexpr int f = 4 - NR / 16;
#pragma unroll
    for (int h = 0; h < 2; ++h) {
        uint32_t A[4][4];
#pragma unroll
        for (int q = 0; q < 4; ++q) {
            const uint32_t ad = pkp + 4 * 64 * (8 * f + 4 * h + q);
            asm volatile("ld.shared.u32 %0, [%1];" : "=r"(A[q][0]) : "r"(ad));
            asm volatile("ld.shared.u32 %0, [%1+32];" : "=r"(A[q][1]) : "r"(ad));
            asm volatile("ld.shared.u32 %0, [%1+-32];" : "=r"(A[q][2]) : "r"(ad));
        }
        wgmma_fence();
#pragma unroll
        for (int q = 0; q < 4; ++q)
            wgmma_rs(acc, A[q][0], A[q][1], A[q][2], A[q][0], make_desc(ubase + 1024 - 128 * (4 * h + q), 16, 256, 3));
        wgmma_commit();
    }
    wgmma_wait<0>();
}
template <int NR>
__device__ __forceinline__ void grow(float (&dst)[NR + 16], const float (&src)[NR]) {
#pragma unroll
    for (int i = 0; i < 16; ++i) dst[i] = 0.f;
#pragma unroll
    for (int i = 0; i < NR; ++i) asm volatile("mov.b32 %0, %1;" : "=f"(dst[16 + i]) : "f"(src[i]));
}

__device__ __forceinline__ void ssm_issue(const CUtensorMap* mapXT, uint32_t sbase, uint32_t bar0, int c, int slot) {
    const uint32_t b = bar0 + 8 * slot;
    mbar_expect_tx(b, 4096 + SS_KB);
    bulk_load(sbase + SS_KBOFF + slot * SS_KB, g_Kb + (size_t)c * KB_PITCH, SS_KB, b);
    tma_load_2d(sbase + ss_u(slot) + 1024, mapXT, 0, c * 128, b);
}
__device__ __forceinline__ void ssm_loop(const bf16* __restrict__ D_skip, const CUtensorMap* mapXT, unsigned char* sm,
                                         uint32_t sbase, uint32_t bar0, int c, uint32_t hread, bool stagger) {
    const int tid = threadIdx.x, warp = tid >> 5, lane = tid & 31;
    const int wg = warp >> 2, wq = warp & 3, tl = tid & 127;
    const int g = lane >> 2, t = lane & 3;
    __shared__ int s_next[3];
    uint32_t* PK = reinterpret_cast<uint32_t*>(sm + ss_pk(wg));
    const uint32_t rbase = sbase + ss_r(wg);
    DBG_T(3, 34);
    *reinterpret_cast<uint4*>(sm + ss_u(2 * wg + (tl >> 6)) + (tl & 63) * 16) = make_uint4(0, 0, 0, 0);
    if (tl < 64) PK[tl] = 0;
    fence_async();
    int rnd_i = 0;
    for (; c < D_; ++rnd_i) {
        const int ch = 2 * wg + (rnd_i & 1);
        const unsigned short* Kb = reinterpret_cast<const unsigned short*>(sm + SS_KBOFF + ch * SS_KB);
        const uint32_t dk = *reinterpret_cast<const unsigned short*>(D_skip + c);
        int nx = 0;
        mbar_wait(bar0 + 8 * ch, (rnd_i >> 1) & 1);
        if (rnd_i == 1) DBG_T(3, 54);
        {
            auto pr = [](uint32_t lo, uint32_t hi) { return lo | (hi << 16); };
            const uint32_t a = Kb[512 + tl], b = Kb[513 + tl];
            uint4 d0, d1;
            if (wq == 0) {
                const uint4 v = *reinterpret_cast<const uint4*>(Kb + 8 * tl);
                const uint32_t pv = tl ? (uint32_t)Kb[8 * tl - 1] : 0u;
                d0 = make_uint4(__byte_perm(v.x, pv, 0x5410), __byte_perm(v.x, v.x, 0x1032), __byte_perm(v.y, v.x, 0x7610), __byte_perm(v.y, v.y, 0x1032));
                d1 = make_uint4(__byte_perm(v.z, v.y, 0x7610), __byte_perm(v.z, v.z, 0x1032), __byte_perm(v.w, v.z, 0x7610), __byte_perm(v.w, v.w, 0x1032));
            } else if (wq == 1) {
                const uint2 v = *reinterpret_cast<const uint2*>(Kb + 128 + 4 * tl);
                const uint32_t t4 = Kb[132 + 4 * tl], pv = Kb[lane ? 128 + 4 * tl : 255];
                const uint32_t t22 = __byte_perm(v.y, v.y, 0x1010);
                d0 = make_uint4(__byte_perm(v.x, pv, 0x5410), __byte_perm(v.x, v.x, 0x1010), __byte_perm(v.x, v.x, 0x1032), __byte_perm(v.y, v.x, 0x7610));
                d1 = make_uint4(t22, t22, __byte_perm(v.y, v.y, 0x1032), __byte_perm(t4, v.y, 0x7610));
            } else {
                const uint32_t v = *reinterpret_cast<const uint32_t*>(Kb + 256 + 2 * tl), t2 = Kb[258 + 2 * tl];
                const uint32_t t00 = __byte_perm(v, v, 0x1010), t11 = __byte_perm(v, v, 0x3232);
                d0 = make_uint4(t00, t00, t00, __byte_perm(v, v, 0x1032));
                d1 = make_uint4(t11, t11, __byte_perm(t2, v, 0x7610), pr(t2, t2));
            }
            uint4* dst = reinterpret_cast<uint4*>(PK + 64 + 8 * tl);
            dst[0] = d0;
            dst[1] = d1;
            const uint32_t mid = tl & 1 ? b : a, aa = pr(a, a), bb = pr(b, b);
            dst[256] = make_uint4(aa, aa, aa, aa);
            dst[257] = make_uint4(pr(mid, a), pr(b, mid), bb, bb);
        }
        if (rnd_i == 1) DBG_T(3, 55);
        named_bar(1 + wg, 128);
        if (rnd_i == 1) DBG_T(3, 56);
        DBG_T(3, 35 + 3 * rnd_i);
        const uint32_t ubase = sbase + ss_u(ch);
        const uint32_t pkp = smem_u32(PK + 64 + 16 * wq + g - 2 * t);
        float acc[64];
        {
            float a3[16], a2[32], a1[48];
#pragma unroll
            for (int i = 0; i < 16; ++i) a3[i] = 0.f;
            if (rnd_i == 0 && wg > 0 && stagger) named_bar(4 + wg, 256);
            conv_phase<16>(a3, pkp, ubase);
            grow<16>(a2, a3);
            conv_phase<32>(a2, pkp, ubase);
            if (rnd_i == 0 && wg < 2 && stagger) asm volatile("bar.arrive %0, 256;" ::"r"(5 + wg) : "memory");
            grow<32>(a1, a2);
            conv_phase<48>(a1, pkp, ubase);
            grow<48>(acc, a1);
            if (tl == 0) asm volatile("atom.relaxed.gpu.global.inc.u32 %0, [%1], 0x7fffffff;" : "=r"(nx) : "l"(&g_ssm_next) : "memory");
            __syncwarp();
            conv_phase<64>(acc, pkp, ubase);
        }
        DBG_T(3, 36 + 3 * rnd_i);
        if (tl == 0) {
            s_next[wg] = nx;
            if (nx < D_) ssm_issue(mapXT, sbase, bar0, nx, ch ^ 1);
        }
        __syncwarp();
        {
            const uint32_t rw = rbase + wq * 4096 + ((lane >> 4) * 8 + (lane & 7)) * 32 + ((((lane >> 3) ^ (lane >> 2)) & 1) << 4);
#pragma unroll
            for (int j = 0; j < 16; j += 2) {
                uint32_t hq[4];
#pragma unroll
                for (int i = 0; i < 4; ++i)
                    asm("cvt.rn.f16x2.f32 %0, %1, %2;" : "=r"(hq[i]) : "f"(acc[4 * j + 2 * i + 1]), "f"(acc[4 * j + 2 * i]));
                asm volatile("stmatrix.sync.aligned.m8n8.x4.trans.shared.b16 [%0], {%1,%2,%3,%4};"
                             ::"r"(rw + j * 256), "r"(hq[0]), "r"(hq[1]), "r"(hq[2]), "r"(hq[3]) : "memory");
            }
        }
        if (rnd_i == 1) DBG_T(3, 57);
        named_bar(1 + wg, 128);
        if (rnd_i == 1) DBG_T(3, 58);
        {
            uint32_t pl[4][8];
#pragma unroll
            for (int w = 0; w < 4; ++w) {
                const int row = tl - w;
                const uint32_t ad = rbase + w * 4096 + row * 32, sw = (row & 4) << 2;
#pragma unroll
                for (int i = 0; i < 8; ++i) pl[w][i] = 0;
                if (row >= 0) {
                    asm volatile("ld.shared.v4.u32 {%0,%1,%2,%3}, [%4];" : "=r"(pl[w][0]), "=r"(pl[w][1]), "=r"(pl[w][2]), "=r"(pl[w][3]) : "r"(ad + sw));
                    asm volatile("ld.shared.v4.u32 {%0,%1,%2,%3}, [%4];" : "=r"(pl[w][4]), "=r"(pl[w][5]), "=r"(pl[w][6]), "=r"(pl[w][7]) : "r"(ad + (sw ^ 16)));
                }
            }
            const uint32_t dsk2 = dk | (dk << 16);
            const unsigned char* xrow = sm + ss_u(ch) + 1024 + tl * 32;
            const int sw = ((tl >> 2) & 1) << 4;
            const uint4 x0 = *reinterpret_cast<const uint4*>(xrow + sw), x1 = *reinterpret_cast<const uint4*>(xrow + (sw ^ 16));
            const uint32_t xv[8] = {x0.x, x0.y, x0.z, x0.w, x1.x, x1.y, x1.z, x1.w};
            uint32_t o[8];
#pragma unroll
            for (int i = 0; i < 8; ++i) {
                const float2 s0 = __half22float2(__hadd2(*reinterpret_cast<const __half2*>(&pl[0][i]), *reinterpret_cast<const __half2*>(&pl[1][i])));
                const float2 s1 = __half22float2(__hadd2(*reinterpret_cast<const __half2*>(&pl[2][i]), *reinterpret_cast<const __half2*>(&pl[3][i])));
                asm("fma.rn.bf16x2 %0, %1, %2, %3;" : "=r"(o[i]) : "r"(pack_bf16(s0.x + s1.x, s0.y + s1.y)), "r"(0x42004200u), "r"(hmul2(xv[i], dsk2)));
            }
            const uint4 o0 = make_uint4(o[0], o[1], o[2], o[3]), o1 = make_uint4(o[4], o[5], o[6], o[7]);
            uint4* dst = reinterpret_cast<uint4*>(g_sT + (size_t)c * L_ + tl * 16);
            dst[0] = o0;
            dst[1] = o1;
        }
        c = s_next[wg];
        DBG_T(3, 37 + 3 * rnd_i);
    }
}

__global__ void __launch_bounds__(384) k_ssm(const __grid_constant__ CUtensorMap mapXT, const bf16* __restrict__ D_skip) {
    extern __shared__ __align__(1024) unsigned char smem_raw[];
    const uint32_t sbase = (smem_u32(smem_raw) + 1023) & ~1023u;
    unsigned char* sm = smem_raw + (sbase - smem_u32(smem_raw));
    __shared__ __align__(8) uint64_t bars[6];
    __shared__ int s_first[3];
    const int tid = threadIdx.x, wg = tid >> 7, tl = tid & 127;
    DBG_T(3, 0);
    if (tid == 32) asm volatile("prefetch.tensormap [%0];" ::"l"(&mapXT) : "memory");
    if (tl == 0) {
        mbar_init(smem_u32(bars + 2 * wg), 1);
        mbar_init(smem_u32(bars + 2 * wg + 1), 1);
        asm volatile("fence.mbarrier_init.release.cluster;" ::: "memory");
        int c;
        asm volatile("atom.relaxed.gpu.global.inc.u32 %0, [%1], 0x7fffffff;" : "=r"(c) : "l"(&g_ssm_next) : "memory");
        unsigned int done = 0;
        for (int it = 0; it < (1 << 22); ++it) {
            asm volatile("ld.acquire.gpu.global.u32 %0, [%1];" : "=r"(done) : "l"(&g_k1_done) : "memory");
            if (done) break;
            __nanosleep(20);
        }
        DBG_P(3, 53);
        s_first[wg] = c;
        if (c < D_) ssm_issue(&mapXT, sbase, smem_u32(bars), c, 2 * wg);
    }
    __syncthreads();
    ssm_loop(D_skip, &mapXT, sm, sbase, smem_u32(bars), s_first[wg], 0,
             s_first[0] < D_ && s_first[1] < D_ && s_first[2] < D_);
    DBG_END(3);
}

#define POLL_NS 300
#define SGO_AT 13
#define XCH 4
#define AHEAD 2
#define GATE_AT (XCH - 2)

template <bool B> struct BoolC { static constexpr bool value = B; };
struct Maps { CUtensorMap A1, B1s, B1p, H, A2, B2, X, S, O, XT; };

__global__ void __launch_bounds__(384, 1) k_main(const __grid_constant__ Maps M, const bf16* __restrict__ bias1,
                                              const bf16* __restrict__ bias2, const bf16* __restrict__ D_skip) {
    extern __shared__ __align__(1024) unsigned char smem_raw[];
    const uint32_t sbase = (smem_u32(smem_raw) + 1023) & ~1023u;
    unsigned char* sm = smem_raw + (sbase - smem_u32(smem_raw));
    __shared__ __align__(8) uint64_t bars[46];
    __shared__ __align__(8) uint64_t dbars[8 * XCH];
    __shared__ __align__(16) uint32_t sbias1[128];
    __shared__ __align__(16) uint32_t sbias[64];
    const uint32_t full0 = smem_u32(bars), empty0 = smem_u32(bars + 4), staged0 = smem_u32(bars + 8);
    const uint32_t xsbar = smem_u32(bars + 16), pfree = smem_u32(bars + 17), mdone = smem_u32(bars + 18), hread = smem_u32(bars + 38), pbar0 = smem_u32(bars + 42);
    const uint32_t ssbar0 = smem_u32(bars + 20), aslot0 = smem_u32(bars + 26), sgo = smem_u32(bars + 29), sbar0 = smem_u32(bars + 30), dready = smem_u32(dbars);
    const int tid = threadIdx.x, warp = tid >> 5, lane = tid & 31;
    const int q = ((blockIdx.x >> 3) + QROT) % 14, rho = blockIdx.x & 7;
    const bool typeP = q < 8;
    const int rank = typeP ? rho & 1 : 0;
    const int nt = q & 1;
    const int mb = typeP ? (q >> 1) * 4 + (rho >> 1) : nt * 8 + rho;
    const int tile = typeP ? nt + 4 * rank : (q >= 12 ? 6 : (q >> 1) - 2);
    const int m0 = mb * 128, n1 = tile * 256;
    const int nsrc = typeP ? 4 : 8;
    const uint16_t mask = typeP ? (uint16_t)(0x55 << rank) : (uint16_t)0xff;
    const int srow0 = typeP ? (rho >> 1) * 16 : rho * 8;
    const int nt0 = nt * 256, n0 = nt0 + rank * 128;
    const uint32_t sx = sbase + 3 * STG, ss = sx + 32768;
    unsigned int* hcnt = g_hcnt + mb * 32;
    DBG_T(0, 0);
    if (tid == 0) pdl_launch();
#define TMPF 0
    if (TMPF && warp == 8 && lane < 10)
        asm volatile("prefetch.tensormap [%0];" ::"l"(reinterpret_cast<const CUtensorMap*>(&M) + lane) : "memory");
    if (warp < 8 && lane == 0) {
#pragma unroll
        for (int c = 0; c < XCH; ++c) {
            mbar_init(dready + 8 * (warp * XCH + c), 1);
            mbar_expect_tx(dready + 8 * (warp * XCH + c), 4096 / XCH);
        }
        mbar_init(staged0 + 8 * warp, 4);
        mbar_init(sbar0 + 8 * warp, 1);
        asm volatile("fence.mbarrier_init.release.cluster;" ::: "memory");
    }
    if (tid == 288) {
        mbar_init(xsbar, 1); mbar_init(sgo, 1); mbar_init(pfree, 2); mbar_init(mdone, 2);
        for (int i = 0; i < 4; ++i) { mbar_init(hread + 8 * i, 2); mbar_init(pbar0 + 8 * i, 1); }
        for (int i = 0; i < 9; ++i) mbar_init(ssbar0 + 8 * i, 1);
        asm volatile("fence.mbarrier_init.release.cluster;" ::: "memory");
    }
    if (tid == 320) {
        for (int s = 0; s < 4; ++s) { mbar_init(full0 + 8 * s, 1); mbar_init(empty0 + 8 * s, 2 * nsrc); }
        asm volatile("fence.mbarrier_init.release.cluster;" ::: "memory");
        for (int k = 0; k < 4; ++k) mbar_expect_tx(full0 + 8 * k, STG + (k == 3 ? 512 : 0));
        bulk_load(smem_u32(sbias1), bias1 + n1, 512, full0 + 24);
    }
    __syncwarp();
    asm volatile("barrier.cluster.arrive.relaxed.aligned;" ::: "memory");
    if (tid == 320) {
        wait_count(g_lncnt + mb, 8);
        for (int k = 0; k < ORD; ++k) tma_load_2d(sbase + k * STG, &M.A1, k * 64, m0, full0 + 8 * k);
    }
    __syncwarp();
    asm volatile("barrier.cluster.wait.acquire.aligned;" ::: "memory");
    const CUtensorMap* mB = typeP ? &M.B1p : &M.B1s;
    auto loadB1 = [&](int k, int s) {
#pragma unroll
        for (int j = 0; j < 4; ++j)
            tma_load_2d_mc(sbase + s * STG + 16384 + j * 8192 + srow0 * 128, mB, n1 + j * 64, k * 64 + srow0, full0 + 8 * s, mask);
    };
#define SDEL 0
    if (tid == 320) {
        if (SDEL && !typeP) __nanosleep(SDEL);
        for (int k = 0; k < 4; ++k) {
#define DLY 2
            if (k == DLY && !typeP) mbar_wait(full0, 0);
            if (k >= ORD) tma_load_2d(sbase + k * STG, &M.A1, k * 64, m0, full0 + 8 * k);
            loadB1(k, k);
        }
    }
    DBG_T(0, 1);
    auto kblock = [&](int j) {
        const int t = j < 4 ? tile : j < 8 ? tile ^ 1 : j < 12 ? 2 + 4 * rank : 3;
        return t * 4 + (j & 3) + (j >= 12 ? 2 * rank : 0);
    };
    auto body = [&](auto tp) {
    constexpr bool TP = decltype(tp)::value;
    if (warp >= 8) {
        if (TP) asm volatile("setmaxnreg.dec.sync.aligned.u32 56;");
        if (warp == 8 && lane == 0) {
            for (int k = 4; k < 8; ++k) {
                const int s = k - 4;
                mbar_wait(empty0 + 8 * s, 0);
                mbar_expect_tx(full0 + 8 * s, STG);
                loadB1(k, s);
                tma_load_2d(sbase + s * STG, &M.A1, k * 64, m0, full0 + 8 * s);
            }
            if (TP) {
                for (int j = 0; j < 14; ++j) {
                    const int s = j < 4 ? j : (j - 4) % 3;
                    const int use = j < 4 ? 2 : 3 + (j - 4) / 3;
                    mbar_wait(empty0 + 8 * s, (use - 1) & 1);
                    mbar_expect_tx(full0 + 8 * s, j < 4 ? 32768 + (j == 0 ? 256 : 0) : STG);
                    if (j >= 4) mbar_arrive(aslot0 + 8 * s);
                    const int kb = kblock(j);
#pragma unroll
                    for (int i = 0; i < 4; ++i)
                        tma_load_2d_mc(sbase + s * STG + 16384 + i * 8192 + srow0 * 128, &M.B2, nt0 + ((i + 2 * rank) & 3) * 64,
                                       kb * 64 + srow0, full0 + 8 * s, mask);
                    if (j == 0) bulk_load(smem_u32(sbias), bias2 + n0, 256, full0);
                    if (j == 6) {
                        mbar_wait(empty0 + 24, 0);
                        mbar_wait(hread + 24, 0);
                        mbar_expect_tx(xsbar, 32768);
                        tma_load_2d(sx, &M.X, n0, m0, xsbar);
                        tma_load_2d(sx + 16384, &M.X, n0 + 64, m0, xsbar);
                    }
#define SGO_E SGO_AT
                    if (j == (nt ? SGO_AT : SGO_E)) mbar_arrive(sgo);
                }
            } else {
                pdl_wait();
                for (int w = 0; w < 3; ++w) ssm_issue(&M.XT, sbase, ssbar0, ((q - 8) * 8 + rho) * 3 + w, 2 * w);
            }
        } else if ((warp == 9 || warp == 10) && lane == 0) {
            const int wg = warp - 9;
            for (int grp = 0; grp < 4; ++grp) {
                mbar_wait(staged0 + 8 * (grp * 2 + wg), 0);
                tma_store_2d(&M.H, sbase + grp * STG + wg * 8192, n1 + grp * 64, m0 + wg * 64);
                asm volatile("cp.async.bulk.commit_group;" ::: "memory");
            }
            asm volatile("cp.async.bulk.wait_group 3;" ::: "memory");
            asm volatile("red.relaxed.gpu.global.add.u32 [%0], 1;" ::"l"(hcnt + tile * 4) : "memory");
            mbar_arrive(hread + 0);
            asm volatile("cp.async.bulk.wait_group 2;" ::: "memory");
            asm volatile("red.relaxed.gpu.global.add.u32 [%0], 1;" ::"l"(hcnt + tile * 4 + 1) : "memory");
            mbar_arrive(hread + 8);
            asm volatile("cp.async.bulk.wait_group 1;" ::: "memory");
            asm volatile("red.relaxed.gpu.global.add.u32 [%0], 1;" ::"l"(hcnt + tile * 4 + 2) : "memory");
            mbar_arrive(hread + 16);
            asm volatile("cp.async.bulk.wait_group 0;" ::: "memory");
            asm volatile("red.relaxed.gpu.global.add.u32 [%0], 1;" ::"l"(hcnt + tile * 4 + 3) : "memory");
            mbar_arrive(hread + 24);
            if (wg == 0) DBG_P(0, 33);
        } else if (warp == 11 && lane == 0 && !TP) {
            if (rho == 0) {
                pdl_wait();
                asm volatile("st.relaxed.gpu.global.u32 [%0], %1;" ::"l"(&g_k1_done), "r"(1u) : "memory");
            }
        } else if (warp == 11 && lane == 0 && TP) {
            uint32_t rdy = 0;
            for (int j = 4; j < 14; ++j) {
                const int s = (j - 4) % 3, kb = kblock(j);
                if ((j & 3) == 0) rdy = 0;
                for (int it = 0; !(rdy >> (kb & 3) & 1) && it < (1 << 22); ++it) {
                    uint4 c4;
                    asm volatile("ld.acquire.gpu.global.v4.u32 {%0,%1,%2,%3}, [%4];" : "=r"(c4.x), "=r"(c4.y), "=r"(c4.z), "=r"(c4.w)
                                 : "l"(hcnt + (kb & ~3)) : "memory");
                    rdy = (c4.x >= 2u) | (c4.y >= 2u) << 1 | (c4.z >= 2u) << 2 | (c4.w >= 2u) << 3;
                }
                if (j == 4) DBG_P(0, 31);
                if (j < 7) mbar_wait(hread + 8 * s, 0);
                mbar_wait(aslot0 + 8 * s, ((j - 4) / 3) & 1);
                tma_load_2d(sbase + s * STG, &M.A2, kb * 64, m0, full0 + 8 * s);
            }
        }
        __syncwarp();
        if (TP && (warp == 9 || warp == 10)) {
            mbar_wait(sgo, 0);
            if (tid == 288) DBG_P(0, 50);
            pdl_wait();
#define PD 250
            if (PD) {
                const int g = (nt * 2 + rank) * 2 + warp - 9;
                if (g >= 5) __nanosleep(PD << (g - 5));
            }
#define PO 0
            const uint32_t t0 = clock();
            const int u0 = 4 * (warp - 9);
            const uint32_t pbar = pbar0 + 8 * (warp - 9);
            uint32_t pend = 15;
            for (int it = 0; pend && it < (1 << 20); ++it) {
                if (lane == 0) {
                    mbar_expect_tx(pbar, 4096 * __popc(pend));
#pragma unroll
                    for (int u = 0; u < 4; ++u)
                        if (pend >> u & 1) {
                            tma_load_2d(ss + (u0 + u) * 2048, &M.S, m0, n0 + (u0 + u) * 16, pbar);
                            tma_load_2d(ss + 16384 + (u0 + u) * 2048, &M.S, m0 + 64, n0 + (u0 + u) * 16, pbar);
                        }
                }
                mbar_wait(pbar, it & 1);
                uint32_t mxs[4];
#pragma unroll
                for (int u = 0; u < 4; ++u) {
                    uint32_t v[8];
#pragma unroll
                    for (int i = 0; i < 8; ++i)
                        asm volatile("ld.shared.u32 %0, [%1];" : "=r"(v[i])
                                     : "r"(ss + (i >> 2) * 16384 + (u0 + u) * 2048 + (i & 3) * 512 + lane * 16 + (lane >> 3) * 4) : "memory");
                    mxs[u] = max(max(max(v[0], v[1]), max(v[2], v[3])), max(max(v[4], v[5]), max(v[6], v[7])));
                }
#pragma unroll
                for (int u = 0; u < 4; ++u)
                    if (pend >> u & 1) {
                        const uint32_t mx = mxs[u];
                        if (!__any_sync(0xffffffffu, mx == 0xffffffffu)) {
                            pend &= ~(1u << u);
                            if (lane == 0) mbar_arrive(sbar0 + 8 * (u0 + u));
                        }
                    }
                fence_async();
                __syncwarp();
                if (PO && it == 0 && pend && nt) {
                    const int g = rank * 2 + warp - 9;
                    const uint32_t d = PO + (g == 0 ? 0 : g == 1 ? 1900 : g == 2 ? 2800 : 4500);
                    while (clock() - t0 < d) __nanosleep(40);
                }
            }
            if (tid == 320) DBG_P(0, 32);
        }
    } else {
        float acc[128];
        const int wg = warp >> 2;
        const uint32_t rem_empty0 = mapa(empty0, TP ? ((lane & 3) << 1) | rank : lane & 7);
        const bool rel = (warp & 3) == 0 && lane < nsrc;
        auto mma_step = [&](int s) {
            const uint32_t sa = sbase + s * STG + wg * 8192, sb = sbase + s * STG + 16384;
            wgmma_fence();
#pragma unroll
            for (int kk = 0; kk < 4; ++kk) wgmma_n256(acc, make_desc(sa + kk * 32, 16, 1024), make_desc(sb + kk * 2048, 8192, 1024));
            wgmma_commit();
        };
#pragma unroll
        for (int i = 0; i < 128; ++i) acc[i] = 0.f;
        for (int k = 0; k < 8; ++k) {
            mbar_wait(full0 + 8 * (k & 3), k >> 2);
            DBG_T(0, 2 + k);
            mma_step(k & 3);
            if (k > 0) {
                wgmma_wait<1>();
                if (rel && (TP || k <= 4)) mbar_arrive_cluster(rem_empty0 + 8 * ((k - 1) & 3));
            }
        }
        wgmma_wait<0>();
        if (TP) { if (rel) mbar_arrive_cluster(rem_empty0 + 24); }
        else if ((tid & 127) == 0) mbar_arrive(mdone);
        DBG_T(0, 10);
        const int srow = wg * 64 + (warp & 3) * 16 + (lane & 7) + ((lane >> 3) & 1) * 8;
        auto hval = [&](int j, int hh) {
            const uint32_t v = hmax2(hadd2(pack_bf16(acc[j * 4 + hh * 2], acc[j * 4 + hh * 2 + 1]), sbias1[j * 4 + (lane & 3)]), 0u);
            return hmul2(v, v);
        };
        auto hstage = [&](int grp, int j, uint32_t r0, uint32_t r1, uint32_t r2, uint32_t r3) {
            const int chunk = (j + (lane >> 4)) & 7;
            stmatrix_x4(sbase + grp * STG + srow * 128 + ((chunk ^ (srow & 7)) << 4), r0, r1, r2, r3);
        };
        auto hdone = [&](int grp) {
            fence_async();
            __syncwarp();
            if (lane == 0) mbar_arrive(staged0 + 8 * (grp * 2 + wg));
        };
        if (!TP) {
#pragma unroll
            for (int grp = 0; grp < 4; ++grp) {
#pragma unroll
                for (int j = 8 * grp; j < 8 * grp + 8; j += 2) hstage(grp, j, hval(j, 0), hval(j, 1), hval(j + 1, 0), hval(j + 1, 1));
                hdone(grp);
            }
            DBG_T(0, 11);
        } else {
        asm volatile("setmaxnreg.inc.sync.aligned.u32 224;");
        uint32_t hp[64];
#pragma unroll
        for (int g2 = 0; g2 < 4; ++g2) {
#pragma unroll
            for (int j = 8 * g2; j < 8 * g2 + 8; ++j) { hp[2 * j] = hval(j, 0); hp[2 * j + 1] = hval(j, 1); }
#pragma unroll
            for (int kk = 0; kk < 4; ++kk)
                hstage(g2, 8 * g2 + 2 * kk, hp[16 * g2 + 4 * kk], hp[16 * g2 + 4 * kk + 1], hp[16 * g2 + 4 * kk + 2], hp[16 * g2 + 4 * kk + 3]);
            hdone(g2);
        }
        DBG_T(0, 11);
#pragma unroll
        for (int i = 0; i < 128; ++i) acc[i] = 0.f;
#pragma unroll
        for (int grp = 0; grp < 4; ++grp) {
            mbar_wait(full0 + 8 * grp, 0);
            DBG_T(0, 12 + grp);
            wgmma_fence();
#pragma unroll
            for (int kk = 0; kk < 4; ++kk)
                wgmma_n256_rs(acc, hp[16 * grp + 4 * kk], hp[16 * grp + 4 * kk + 1], hp[16 * grp + 4 * kk + 2], hp[16 * grp + 4 * kk + 3],
                              make_desc(sbase + grp * STG + 16384 + kk * 2048, 8192, 1024));
            wgmma_commit();
            if (grp > 0) {
                wgmma_wait<1>();
                if (rel) mbar_arrive_cluster(rem_empty0 + 8 * (grp - 1));
            }
        }
        {
            const uint32_t sig = mapa(pfree, rho ^ 1);
            int s = 0, sp = 3;
            uint32_t par = 1;
            for (int j = 4; j < 14; ++j) {
                mbar_wait(full0 + 8 * s, par);
                DBG_T(0, 12 + j);
                mma_step(s);
                wgmma_wait<1>();
                if (rel && j <= 11) mbar_arrive_cluster(rem_empty0 + 8 * sp);
                if (j == 13 && (tid & 127) == 0) mbar_arrive_cluster(sig);
                sp = s;
                ++s;
                if (s == 3) { s = 0; par ^= 1; }
            }
        }
        auto xo = [&](int j) { return sx + (j >> 3) * 16384 + srow * 128 + ((((j + (lane >> 4)) & 7) ^ (srow & 7)) << 4); };
        uint32_t xr[32];
        mbar_wait(xsbar, 0);
#pragma unroll
        for (int j = 0; j < 16; j += 2) ldmatrix_x4(xr[2 * j], xr[2 * j + 1], xr[2 * j + 2], xr[2 * j + 3], xo(j));
        wgmma_wait<0>();
        DBG_T(0, 26);
        constexpr int JC = 16 / XCH;
        const uint32_t xoff = sbase + STG + (warp >> 2) * STG + (warp & 3) * 8192 + lane * 16;
        const uint32_t dstw = mapa(xoff, rho ^ 1);
        const uint32_t rbar = mapa(dready + 8 * warp * XCH, rho ^ 1);
        auto pk = [](float a, float b) {
            uint32_t r;
            asm("cvt.rn.f16x2.f32 %0, %1, %2;" : "=r"(r) : "f"(b * 0.015625f), "f"(a * 0.015625f));
            return r;
        };
        auto send = [&](int j) {
            if (j & 1) return;
            asm volatile("st.async.weak.shared::cluster.mbarrier::complete_tx::bytes.v4.b32 [%0], {%1,%2,%3,%4}, [%5];"
                         ::"r"(dstw + j * 256), "r"(pk(acc[64 + 4 * j], acc[65 + 4 * j])), "r"(pk(acc[66 + 4 * j], acc[67 + 4 * j])),
                           "r"(pk(acc[68 + 4 * j], acc[69 + 4 * j])), "r"(pk(acc[70 + 4 * j], acc[71 + 4 * j])),
                           "r"(rbar + 8 * (j / JC)) : "memory");
        };
        mbar_wait(pfree, 0);
#pragma unroll
        for (int j = 0; j < AHEAD * JC; ++j) send(j);
        DBG_T(0, 27);
        uint32_t gq[32];
        auto sload = [&](int j, uint32_t (&sr)[4]) {
            const int crow = (j + (lane >> 4)) * 8 + (lane & 7);
            const int lch = (warp & 3) * 2 + ((lane >> 3) & 1);
            asm volatile("ldmatrix.sync.aligned.m8n8.x4.trans.shared.b16 {%0,%1,%2,%3}, [%4];"
                         : "=r"(sr[0]), "=r"(sr[1]), "=r"(sr[2]), "=r"(sr[3])
                         : "r"(ss + wg * 16384 + crow * 128 + ((lch ^ (crow & 7)) << 4)));
        };
        auto gate2 = [&](int j, const uint32_t (&sr)[4]) {
            uint32_t r[4];
#pragma unroll
            for (int q = 0; q < 4; ++q) r[q] = hadd2(xr[2 * j + q], hmul2(sr[q], gq[2 * j + q]));
            stmatrix_x4(xo(j), r[0], r[1], r[2], r[3]);
        };
        auto ostore = [&](int grp) {
            fence_async();
            __syncwarp();
            if (lane == 0) {
                tma_store_2d(&M.O, sx + grp * 16384 + warp * 2048, n0 + grp * 64, m0 + warp * 16);
                asm volatile("cp.async.bulk.commit_group;" ::: "memory");
            }
        };
        uint32_t todo = 3, hv[4];
#pragma unroll 1
        for (int att = 0; todo; ++att) {
#pragma unroll
            for (int grp = 0; grp < 2; ++grp) {
                if (att == 0) {
#pragma unroll
                    for (int c = 2 * grp; c < 2 * grp + 2; ++c) {
                        mbar_wait(dready + 8 * (warp * XCH + c), 0);
#pragma unroll
                        for (int j = 4 * c; j < 4 * c + 4; ++j) {
                            if (c + AHEAD < XCH) send(j + AHEAD * JC);
                            if ((j & 1) == 0)
                                asm volatile("ld.shared.v4.b32 {%0,%1,%2,%3}, [%4];" : "=r"(hv[0]), "=r"(hv[1]), "=r"(hv[2]), "=r"(hv[3])
                                             : "r"(xoff + j * 256));
                            const float2 va = __half22float2(*reinterpret_cast<const __half2*>(&hv[2 * (j & 1)]));
                            const float2 vb = __half22float2(*reinterpret_cast<const __half2*>(&hv[2 * (j & 1) + 1]));
                            const uint32_t bh = hmul2(sbias[j * 4 + (lane & 3)], 0x3f003f00u);
                            const uint32_t v0 = hfma2(pack_bf16(fmaf(va.x, 64.f, acc[4 * j]), fmaf(va.y, 64.f, acc[4 * j + 1])), 0x3f003f00u, bh);
                            const uint32_t v1 = hfma2(pack_bf16(fmaf(vb.x, 64.f, acc[4 * j + 2]), fmaf(vb.y, 64.f, acc[4 * j + 3])), 0x3f003f00u, bh);
                            gq[2 * j] = pack_bf16(silu_h(__uint_as_float(v0 << 16)), silu_h(__uint_as_float(v0 & 0xffff0000u)));
                            gq[2 * j + 1] = pack_bf16(silu_h(__uint_as_float(v1 << 16)), silu_h(__uint_as_float(v1 & 0xffff0000u)));
                        }
                    }
                    if (grp == 1) DBG_T(0, 28);
                }
                if (todo >> grp & 1) {
                    const bool last = todo == (1u << grp) && (grp == 1 || att > 0);
                    bool go;
                    int it = 0;
                    do {
                        uint32_t ok;
                        asm volatile("{\n.reg .pred p;\nmbarrier.test_wait.parity.shared::cta.b64 p, [%1], 0;\nselp.u32 %0, 1, 0, p;\n}\n"
                                     : "=r"(ok) : "r"(sbar0 + 8 * (4 * grp + (lane & 3))) : "memory");
                        go = __all_sync(0xffffffffu, ok) || att > (1 << 22);
                    } while (!go && last && ++it < (1 << 24));
                    if (go || last) {
                        uint32_t sr[4][4];
#pragma unroll
                        for (int u = 0; u < 4; ++u) sload(8 * grp + 2 * u, sr[u]);
#pragma unroll
                        for (int u = 0; u < 4; ++u) gate2(8 * grp + 2 * u, sr[u]);
                        ostore(grp);
                        todo &= ~(1u << grp);
                        if (grp == 0) DBG_T(0, 29);
                    }
                }
            }
        }
        if (lane == 0) asm volatile("cp.async.bulk.wait_group.read 0;" ::: "memory");
        DBG_T(0, 30);
        }
    }
    if (!TP) {
        mbar_wait(mdone, 0);
        ssm_loop(D_skip, &M.XT, sm, sbase, ssbar0, ((q - 8) * 8 + rho) * 3 + (warp >> 2), hread, true);
    }
    DBG_END(0);
    };
    if (typeP) body(BoolC<true>{});
    else body(BoolC<false>{});
}

typedef CUresult (*PFN_encodeTiled)(CUtensorMap*, CUtensorMapDataType, cuuint32_t, void*, const cuuint64_t*,
                                    const cuuint64_t*, const cuuint32_t*, const cuuint32_t*, CUtensorMapInterleave,
                                    CUtensorMapSwizzle, CUtensorMapL2promotion, CUtensorMapFloatOOBfill);

static void make_map(PFN_encodeTiled enc, CUtensorMap* m, const void* ptr, uint64_t inner, uint64_t outer,
                     uint32_t box_inner, uint32_t box_outer, CUtensorMapSwizzle swz) {
    cuuint64_t dims[2] = {inner, outer};
    cuuint64_t strides[1] = {inner * 2};
    cuuint32_t box[2] = {box_inner, box_outer};
    cuuint32_t es[2] = {1, 1};
    enc(m, CU_TENSOR_MAP_DATA_TYPE_BFLOAT16, 2, const_cast<void*>(ptr), dims, strides, box, es,
        CU_TENSOR_MAP_INTERLEAVE_NONE, swz, CU_TENSOR_MAP_L2_PROMOTION_L2_256B, CU_TENSOR_MAP_FLOAT_OOB_FILL_NONE);
}

template <typename... KArgs, typename... Args>
static void launch_cluster(void (*k)(KArgs...), dim3 grid, dim3 block, int smem, dim3 cluster, Args... args) {
    cudaLaunchConfig_t cfg = {};
    cfg.gridDim = grid;
    cfg.blockDim = block;
    cfg.dynamicSmemBytes = smem;
    cfg.stream = cudaStreamPerThread;
    cudaLaunchAttribute at[2];
    at[0].id = cudaLaunchAttributeClusterDimension;
    at[0].val.clusterDim.x = cluster.x;
    at[0].val.clusterDim.y = cluster.y;
    at[0].val.clusterDim.z = cluster.z;
    at[1].id = cudaLaunchAttributeProgrammaticStreamSerialization;
    at[1].val.programmaticStreamSerializationAllowed = 1;
    cfg.attrs = at;
    cfg.numAttrs = 2;
    cudaLaunchKernelEx(&cfg, k, KArgs(args)...);
}

extern "C" void kernel_launch(void* const* d_in, const int* in_sizes, int n_in, void* d_out, int out_size) {
    const bf16* x = (const bf16*)d_in[0];
    const bf16* log_A_real = (const bf16*)d_in[1];
    const bf16* A_imag = (const bf16*)d_in[2];
    const bf16* C_real = (const bf16*)d_in[3];
    const bf16* C_imag = (const bf16*)d_in[4];
    const bf16* log_dt = (const bf16*)d_in[5];
    const bf16* D_skip = (const bf16*)d_in[6];
    const bf16* w1 = (const bf16*)d_in[8];
    const bf16* b1 = (const bf16*)d_in[9];
    const bf16* w2 = (const bf16*)d_in[10];
    const bf16* b2 = (const bf16*)d_in[11];
    bf16* out = (bf16*)d_out;

    static bool init = false;
    static Maps M;
    if (!init) {
        void* fn = nullptr;
        void *p_xn, *p_h, *p_s, *p_xt;
        cudaGetSymbolAddress(&p_xt, g_xT);
        cudaGetSymbolAddress(&p_s, g_sT);
        cudaDriverEntryPointQueryResult qr;
        cudaGetDriverEntryPoint("cuTensorMapEncodeTiled", &fn, cudaEnableDefault, &qr);
        PFN_encodeTiled enc = (PFN_encodeTiled)fn;
        cudaGetSymbolAddress(&p_xn, g_xn);
        cudaGetSymbolAddress(&p_h, g_h);
        make_map(enc, &M.A1, p_xn, D_, L_, 64, 128, CU_TENSOR_MAP_SWIZZLE_128B);
        make_map(enc, &M.B1s, w1, F_, D_, 64, 8, CU_TENSOR_MAP_SWIZZLE_128B);
        make_map(enc, &M.B1p, w1, F_, D_, 64, 16, CU_TENSOR_MAP_SWIZZLE_128B);
        make_map(enc, &M.A2, p_h, F_, L_, 64, 128, CU_TENSOR_MAP_SWIZZLE_128B);
        make_map(enc, &M.B2, w2, D_, F_, 64, 16, CU_TENSOR_MAP_SWIZZLE_128B);
        make_map(enc, &M.H, p_h, F_, L_, 64, 64, CU_TENSOR_MAP_SWIZZLE_128B);
        make_map(enc, &M.X, x, D_, L_, 64, 128, CU_TENSOR_MAP_SWIZZLE_128B);
        make_map(enc, &M.S, p_s, L_, D_, 64, 16, CU_TENSOR_MAP_SWIZZLE_128B);
        make_map(enc, &M.O, out, D_, L_, 64, 16, CU_TENSOR_MAP_SWIZZLE_128B);
        make_map(enc, &M.XT, p_xt, 16, D_ * 128, 16, 128, CU_TENSOR_MAP_SWIZZLE_32B);
        cudaFuncSetAttribute(k1_prep, cudaFuncAttributePreferredSharedMemoryCarveout, 100);
        cudaFuncSetAttribute(k_main, cudaFuncAttributeMaxDynamicSharedMemorySize, MAIN_SMEM);
        cudaFuncSetAttribute(k_ssm, cudaFuncAttributeMaxDynamicSharedMemorySize, MAIN_SMEM);
        init = true;
    }
    SsmParams P{log_A_real, A_imag, C_real, C_imag, log_dt, D_skip};
    k1_prep<<<K1_BLOCKS, 128 * K1W>>>(x, P, w1, w2);
    launch_cluster(k_main, dim3(112), dim3(384), MAIN_SMEM, dim3(8, 1, 1), M, b1, b2, D_skip);
    launch_cluster(k_ssm, dim3(20), dim3(384), MAIN_SMEM, dim3(1, 1, 1), M.XT, D_skip);
}
```
